```python
import torch

def _softmax(x, axis=-1):
    return torch.softmax(x, dim=axis)
def _gelu(x):
    return torch.nn.functional.gelu(x, approximate="tanh")
def _silu(x):
    return torch.nn.functional.silu(x)
def _sigmoid(x):
    return torch.sigmoid(x)
def _layernorm(x, axis=-1, eps=1e-5):
    m = x.mean(dim=axis, keepdim=True)
    v = x.var(dim=axis, keepdim=True, unbiased=False)
    return (x - m) / torch.sqrt(v + eps)
def _scatter_add(tgt, idx, src, axis=0):
    return tgt.clone().index_add_(axis, idx, src)
def _segment_sum(src, seg, n):
    out = torch.zeros((n,) + src.shape[1:], dtype=src.dtype)
    return out.index_add_(0, seg, src)
def _pad(x, pw):
    flat = tuple(v for pair in reversed(pw) for v in pair)
    return torch.nn.functional.pad(x, flat)

kernel_name = 'interleave_layers__spectral_gfnet__mixer_token_mlp__prompt'

def setup_inputs():

    _w = (lambda a: (lambda t: t.to(torch.bfloat16) if t.is_floating_point() else t)(torch.as_tensor(a)))
    def _A_setup():
        B, S, D = 1, 2048, 512
        Df = D // 2 + 1
        return {
            "x": _w((lambda *s: torch.randn(*s, dtype=torch.bfloat16) * 0.05)(B, S, D)),
            "w_r": _w((lambda *s: torch.randn(*s, dtype=torch.bfloat16) * 0.8)(S, Df) * 0.02),
            "w_i": _w((lambda *s: torch.randn(*s, dtype=torch.bfloat16) * 0.8)(S, Df) * 0.02),
        }
    _A_in = _A_setup()

    def _B_setup():
        B, S, D, F = 1, 2048, 512, 1792
        return {
            "x": _w((lambda *s: torch.randn(*s, dtype=torch.bfloat16) * 0.05)(B, S, D)),
            "w1": _w((lambda *s: torch.randn(*s, dtype=torch.bfloat16) * 0.4)(S, F) * (S ** -0.5)),
            "b1": _w((lambda *s: torch.randn(*s, dtype=torch.bfloat16) * 3.2)(F) * 0.02),
            "w2": _w((lambda *s: torch.randn(*s, dtype=torch.bfloat16) * 0.4)(F, S) * (F ** -0.5)),
            "b2": _w((lambda *s: torch.randn(*s, dtype=torch.bfloat16) * 1.6)(S) * 0.02),
        }
    _B_in = _B_setup()

    return {
        "A_x": _A_in["x"],
        "A_w_r": _A_in["w_r"],
        "A_w_i": _A_in["w_i"],
        "B_x": _B_in["x"],
        "B_w1": _B_in["w1"],
        "B_b1": _B_in["b1"],
        "B_w2": _B_in["w2"],
        "B_b2": _B_in["b2"],
    }

def reference(A_x, A_w_r, A_w_i, B_x, B_w1, B_b1, B_w2, B_b2):
    def _A_ref(x, w_r, w_i):
        B, S, D = x.shape
        X = (lambda x, axes=(-2,-1): torch.fft.rfft2(x.float(), dim=axes))(x, axes=(-2, -1))
        W = w_r + 1j * w_i
        X = X * W
        y = (lambda x, s, axes=(-2,-1): torch.fft.irfft2(x, s=s, dim=axes).to(torch.bfloat16))(X, (S, D), axes=(-2, -1))
        return y

    def _B_ref(x, w1, b1, w2, b2):
        B, S, D = x.shape
        h = _layernorm(x, axis=-1)
        u = torch.einsum("bsd,sf->bdf", h, w1) + b1
        u = _gelu(u)
        y = torch.einsum("bdf,fs->bds", u, w2) + b2
        return (lambda x, *d: x.permute(*d))(y, 0, 2, 1)

    x = A_x
    x = x + _A_ref(_layernorm(x, axis=-1), A_w_r, A_w_i)
    x = x + _B_ref(_layernorm(x, axis=-1), B_w1, B_b1, B_w2, B_b2)
    x = x + _A_ref(_layernorm(x, axis=-1), A_w_r, A_w_i)
    x = x + _B_ref(_layernorm(x, axis=-1), B_w1, B_b1, B_w2, B_b2)
    return x
```

```cpp
#include <cuda_runtime.h>
#include <cuda_bf16.h>
#include <cuda_fp16.h>
#include <cuda.h>
#include <stdint.h>

namespace {

constexpr int S_ = 2048, D_ = 512, F_ = 1792, DF_ = 257;

__device__ __align__(16) uint32_t g_T[256 * 2048];
__device__ __align__(16) uint32_t g_Wt[256 * 2048];
__device__ __align__(16) uint32_t g_Wn[2 * 2048];
__device__ __align__(16) uint32_t g_T0[128 * 16];
__device__ __align__(16) uint32_t g_wmax[128];
constexpr int R_THREADS = 512;
constexpr int FLAG_PITCH = 32;
__device__ unsigned g_flags[2 * 28 * 8 * FLAG_PITCH];
__device__ __align__(1024) __nv_bfloat16 g_X1[S_ * D_];
__device__ __align__(1024) __nv_bfloat16 g_H[S_ * D_];
__device__ __align__(1024) __nv_bfloat16 g_U[F_ * D_];
__device__ __align__(1024) __nv_bfloat16 g_X2[S_ * D_];

__device__ __forceinline__ uint32_t smem_u32(const void* p) { return (uint32_t)__cvta_generic_to_shared(p); }
__device__ __forceinline__ void pdl_wait() { asm volatile("griddepcontrol.wait;" ::: "memory"); }
__device__ __forceinline__ void pdl_wait_after_loads(void* smem_word) {
  asm volatile("st.volatile.shared.u32 [%0], %1;\ngriddepcontrol.wait;" ::"r"(smem_u32(smem_word)), "r"(0) : "memory");
}
__device__ __forceinline__ void pdl_launch() { asm volatile("griddepcontrol.launch_dependents;" ::: "memory"); }
__device__ __forceinline__ uint32_t ldg_u32(const void* p) { uint32_t v; asm volatile("ld.global.b32 %0, [%1];" : "=r"(v) : "l"(p)); return v; }
__device__ __forceinline__ void ldg_u64(const void* p, uint32_t& a, uint32_t& b) { asm volatile("ld.global.v2.b32 {%0,%1}, [%2];" : "=r"(a), "=r"(b) : "l"(p)); }
__device__ __forceinline__ uint4 ldg_u128(const void* p) { uint4 v; asm volatile("ld.global.v4.b32 {%0,%1,%2,%3}, [%4];" : "=r"(v.x), "=r"(v.y), "=r"(v.z), "=r"(v.w) : "l"(p)); return v; }
__device__ __forceinline__ float bf16r(float x) {
  uint32_t u;
  asm("cvt.rn.bf16x2.f32 %0, %1, %2;" : "=r"(u) : "f"(x), "f"(0.f));
  return __uint_as_float(u & 0xffff0000u);
}
__device__ __forceinline__ float2 bf2_to_f2(uint32_t u) {
  return make_float2(__uint_as_float(u << 16), __uint_as_float(u & 0xffff0000u));
}
__device__ __forceinline__ uint32_t f2_to_bf2(float a, float b) {
  __nv_bfloat162 h = __floats2bfloat162_rn(a, b);
  return *reinterpret_cast<uint32_t*>(&h);
}
__device__ __forceinline__ uint32_t bf2_add(uint32_t a, uint32_t b) {
  __nv_bfloat162 r = __hadd2(*reinterpret_cast<__nv_bfloat162*>(&a), *reinterpret_cast<__nv_bfloat162*>(&b));
  return *reinterpret_cast<uint32_t*>(&r);
}
__device__ __forceinline__ uint32_t f2_to_h2(float2 a) {
  __half2 h = __floats2half2_rn(a.x, a.y);
  return *reinterpret_cast<uint32_t*>(&h);
}
__device__ __forceinline__ float2 cmul(float2 a, float2 b) {
  return make_float2(a.x * b.x - a.y * b.y, a.x * b.y + a.y * b.x);
}
__device__ const uint4 c_lane[14 * 32] = {
  {0x00003400u,0x00003400u,0x00003400u,0x00003400u}, {0x00003400u,0x00003400u,0x34000000u,0x34000000u}, {0x00003400u,0x00003400u,0x0000b400u,0x0000b400u}, {0x00003400u,0x00003400u,0xb4008000u,0xb4008000u}, {0x34008000u,0x34008000u,0x34008000u,0x34008000u}, {0x34008000u,0x34008000u,0x0000b400u,0x0000b400u}, {0x34008000u,0x34008000u,0xb4008000u,0xb4008000u}, {0x34008000u,0x34008000u,0x80003400u,0x80003400u}, {0x00003400u,0x34000000u,0x00003400u,0x34000000u}, {0x2e1f3364u,0x3364ae1fu,0x3364ae1fu,0xae1fb364u}, {0x31a831a8u,0x31a8b1a8u,0xb1a8b1a8u,0xb1a831a8u}, {0x33642e1fu,0x2e1fb364u,0xae1f3364u,0x33642e1fu}, {0x34008000u,0x0000b400u,0x34008000u,0x0000b400u}, {0x3364ae1fu,0xae1fb364u,0xae1fb364u,0xb3642e1fu}, {0x31a8b1a8u,0xb1a8b1a8u,0xb1a831a8u,0x31a831a8u}, {0x2e1fb364u,0xb364ae1fu,0x33642e1fu,0x2e1fb364u}, {0x00003400u,0x0000b400u,0x00003400u,0x0000b400u}, {0x31a831a8u,0xb1a8b1a8u,0x31a8b1a8u,0xb1a831a8u}, {0x34000000u,0xb4008000u,0xb4008000u,0x34000000u}, {0x31a8b1a8u,0xb1a831a8u,0x31a831a8u,0xb1a8b1a8u}, {0x34008000u,0xb4008000u,0x34008000u,0xb4008000u}, {0x31a8b1a8u,0xb1a831a8u,0xb1a8b1a8u,0x31a831a8u}, {0x0000b400u,0x80003400u,0x80003400u,0x0000b400u}, {0xb1a8b1a8u,0x31a831a8u,0x31a8b1a8u,0xb1a831a8u}, {0x00003400u,0xb4008000u,0x00003400u,0xb4008000u}, {0x33642e1fu,0xae1f3364u,0x2e1fb364u,0x33642e1fu}, {0x31a8b1a8u,0x31a831a8u,0xb1a831a8u,0xb1a8b1a8u}, {0xae1fb364u,0x3364ae1fu,0x3364ae1fu,0x2e1f3364u}, {0x34008000u,0x80003400u,0x34008000u,0x80003400u}, {0x2e1fb364u,0x33642e1fu,0xb364ae1fu,0x2e1fb364u}, {0xb1a8b1a8u,0x31a8b1a8u,0x31a831a8u,0xb1a831a8u}, {0xb3642e1fu,0xae1fb364u,0xae1fb364u,0x3364ae1fu},
  {0x00003400u,0x00003400u,0x00003400u,0x00003400u}, {0x0000b400u,0x0000b400u,0xb4008000u,0xb4008000u}, {0x00003400u,0x00003400u,0x0000b400u,0x0000b400u}, {0x0000b400u,0x0000b400u,0x34000000u,0x34000000u}, {0x34008000u,0x34008000u,0x34008000u,0x34008000u}, {0xb4008000u,0xb4008000u,0x80003400u,0x80003400u}, {0x34008000u,0x34008000u,0xb4008000u,0xb4008000u}, {0xb4008000u,0xb4008000u,0x0000b400u,0x0000b400u}, {0x00003400u,0x34000000u,0x00003400u,0x34000000u}, {0xae1fb364u,0xb3642e1fu,0xb3642e1fu,0x2e1f3364u}, {0x31a831a8u,0x31a8b1a8u,0xb1a8b1a8u,0xb1a831a8u}, {0xb364ae1fu,0xae1f3364u,0x2e1fb364u,0xb364ae1fu}, {0x34008000u,0x0000b400u,0x34008000u,0x0000b400u}, {0xb3642e1fu,0x2e1f3364u,0x2e1f3364u,0x3364ae1fu}, {0x31a8b1a8u,0xb1a8b1a8u,0xb1a831a8u,0x31a831a8u}, {0xae1f3364u,0x33642e1fu,0xb364ae1fu,0xae1f3364u}, {0x00003400u,0x0000b400u,0x00003400u,0x0000b400u}, {0xb1a8b1a8u,0x31a831a8u,0xb1a831a8u,0x31a8b1a8u}, {0x34000000u,0xb4008000u,0xb4008000u,0x34000000u}, {0xb1a831a8u,0x31a8b1a8u,0xb1a8b1a8u,0x31a831a8u}, {0x34008000u,0xb4008000u,0x34008000u,0xb4008000u}, {0xb1a831a8u,0x31a8b1a8u,0x31a831a8u,0xb1a8b1a8u}, {0x0000b400u,0x80003400u,0x80003400u,0x0000b400u}, {0x31a831a8u,0xb1a8b1a8u,0xb1a831a8u,0x31a8b1a8u}, {0x00003400u,0xb4008000u,0x00003400u,0xb4008000u}, {0xb364ae1fu,0x2e1fb364u,0xae1f3364u,0xb364ae1fu}, {0x31a8b1a8u,0x31a831a8u,0xb1a831a8u,0xb1a8b1a8u}, {0x2e1f3364u,0xb3642e1fu,0xb3642e1fu,0xae1fb364u}, {0x34008000u,0x80003400u,0x34008000u,0x80003400u}, {0xae1f3364u,0xb364ae1fu,0x33642e1fu,0xae1f3364u}, {0xb1a8b1a8u,0x31a8b1a8u,0x31a831a8u,0xb1a831a8u}, {0x3364ae1fu,0x2e1f3364u,0x2e1f3364u,0xb3642e1fu},
  {0x00003400u,0x00003400u,0x00003400u,0x00003400u}, {0x00003400u,0x00003400u,0x34000000u,0x34000000u}, {0x00003400u,0x00003400u,0x0000b400u,0x0000b400u}, {0x00003400u,0x00003400u,0xb4008000u,0xb4008000u}, {0x34008000u,0x34008000u,0x34008000u,0x34008000u}, {0x34008000u,0x34008000u,0x0000b400u,0x0000b400u}, {0x34008000u,0x34008000u,0xb4008000u,0xb4008000u}, {0x34008000u,0x34008000u,0x80003400u,0x80003400u}, {0x0000b400u,0xb4008000u,0x0000b400u,0xb4008000u}, {0xae1fb364u,0xb3642e1fu,0xb3642e1fu,0x2e1f3364u}, {0xb1a8b1a8u,0xb1a831a8u,0x31a831a8u,0x31a8b1a8u}, {0xb364ae1fu,0xae1f3364u,0x2e1fb364u,0xb364ae1fu}, {0xb4008000u,0x80003400u,0xb4008000u,0x80003400u}, {0xb3642e1fu,0x2e1f3364u,0x2e1f3364u,0x3364ae1fu}, {0xb1a831a8u,0x31a831a8u,0x31a8b1a8u,0xb1a8b1a8u}, {0xae1f3364u,0x33642e1fu,0xb364ae1fu,0xae1f3364u}, {0x00003400u,0x0000b400u,0x00003400u,0x0000b400u}, {0x31a831a8u,0xb1a8b1a8u,0x31a8b1a8u,0xb1a831a8u}, {0x34000000u,0xb4008000u,0xb4008000u,0x34000000u}, {0x31a8b1a8u,0xb1a831a8u,0x31a831a8u,0xb1a8b1a8u}, {0x34008000u,0xb4008000u,0x34008000u,0xb4008000u}, {0x31a8b1a8u,0xb1a831a8u,0xb1a8b1a8u,0x31a831a8u}, {0x0000b400u,0x80003400u,0x80003400u,0x0000b400u}, {0xb1a8b1a8u,0x31a831a8u,0x31a8b1a8u,0xb1a831a8u}, {0x0000b400u,0x34000000u,0x0000b400u,0x34000000u}, {0xb364ae1fu,0x2e1fb364u,0xae1f3364u,0xb364ae1fu}, {0xb1a831a8u,0xb1a8b1a8u,0x31a8b1a8u,0x31a831a8u}, {0x2e1f3364u,0xb3642e1fu,0xb3642e1fu,0xae1fb364u}, {0xb4008000u,0x0000b400u,0xb4008000u,0x0000b400u}, {0xae1f3364u,0xb364ae1fu,0x33642e1fu,0xae1f3364u}, {0x31a831a8u,0xb1a831a8u,0xb1a8b1a8u,0x31a8b1a8u}, {0x3364ae1fu,0x2e1f3364u,0x2e1f3364u,0xb3642e1fu},
  {0x00003400u,0x00003400u,0x00003400u,0x00003400u}, {0x0000b400u,0x0000b400u,0xb4008000u,0xb4008000u}, {0x00003400u,0x00003400u,0x0000b400u,0x0000b400u}, {0x0000b400u,0x0000b400u,0x34000000u,0x34000000u}, {0x34008000u,0x34008000u,0x34008000u,0x34008000u}, {0xb4008000u,0xb4008000u,0x80003400u,0x80003400u}, {0x34008000u,0x34008000u,0xb4008000u,0xb4008000u}, {0xb4008000u,0xb4008000u,0x0000b400u,0x0000b400u}, {0x0000b400u,0xb4008000u,0x0000b400u,0xb4008000u}, {0x2e1f3364u,0x3364ae1fu,0x3364ae1fu,0xae1fb364u}, {0xb1a8b1a8u,0xb1a831a8u,0x31a831a8u,0x31a8b1a8u}, {0x33642e1fu,0x2e1fb364u,0xae1f3364u,0x33642e1fu}, {0xb4008000u,0x80003400u,0xb4008000u,0x80003400u}, {0x3364ae1fu,0xae1fb364u,0xae1fb364u,0xb3642e1fu}, {0xb1a831a8u,0x31a831a8u,0x31a8b1a8u,0xb1a8b1a8u}, {0x2e1fb364u,0xb364ae1fu,0x33642e1fu,0x2e1fb364u}, {0x00003400u,0x0000b400u,0x00003400u,0x0000b400u}, {0xb1a8b1a8u,0x31a831a8u,0xb1a831a8u,0x31a8b1a8u}, {0x34000000u,0xb4008000u,0xb4008000u,0x34000000u}, {0xb1a831a8u,0x31a8b1a8u,0xb1a8b1a8u,0x31a831a8u}, {0x34008000u,0xb4008000u,0x34008000u,0xb4008000u}, {0xb1a831a8u,0x31a8b1a8u,0x31a831a8u,0xb1a8b1a8u}, {0x0000b400u,0x80003400u,0x80003400u,0x0000b400u}, {0x31a831a8u,0xb1a8b1a8u,0xb1a831a8u,0x31a8b1a8u}, {0x0000b400u,0x34000000u,0x0000b400u,0x34000000u}, {0x33642e1fu,0xae1f3364u,0x2e1fb364u,0x33642e1fu}, {0xb1a831a8u,0xb1a8b1a8u,0x31a8b1a8u,0x31a831a8u}, {0xae1fb364u,0x3364ae1fu,0x3364ae1fu,0x2e1f3364u}, {0xb4008000u,0x0000b400u,0xb4008000u,0x0000b400u}, {0x2e1fb364u,0x33642e1fu,0xb364ae1fu,0x2e1fb364u}, {0x31a831a8u,0xb1a831a8u,0xb1a8b1a8u,0x31a8b1a8u}, {0xb3642e1fu,0xae1fb364u,0xae1fb364u,0x3364ae1fu},
  {0x00003400u,0x00003400u,0x00003400u,0x00003400u}, {0x00003400u,0x00003400u,0x0000b400u,0x0000b400u}, {0x00003400u,0x00003400u,0x00003400u,0x00003400u}, {0x00003400u,0x00003400u,0x0000b400u,0x0000b400u}, {0x34008000u,0x34008000u,0x34008000u,0x34008000u}, {0x34008000u,0x34008000u,0xb4008000u,0xb4008000u}, {0x34008000u,0x34008000u,0x34008000u,0x34008000u}, {0x34008000u,0x34008000u,0xb4008000u,0xb4008000u}, {0x00003400u,0x0000b400u,0x00003400u,0x0000b400u}, {0x31a831a8u,0xb1a8b1a8u,0xb1a8b1a8u,0x31a831a8u}, {0x34000000u,0xb4008000u,0x34000000u,0xb4008000u}, {0x31a8b1a8u,0xb1a831a8u,0xb1a831a8u,0x31a8b1a8u}, {0x34008000u,0xb4008000u,0x34008000u,0xb4008000u}, {0x31a8b1a8u,0xb1a831a8u,0xb1a831a8u,0x31a8b1a8u}, {0x0000b400u,0x80003400u,0x0000b400u,0x80003400u}, {0xb1a8b1a8u,0x31a831a8u,0x31a831a8u,0xb1a8b1a8u}, {0x00003400u,0x00003400u,0x00003400u,0x00003400u}, {0x34000000u,0x34000000u,0xb4008000u,0xb4008000u}, {0x0000b400u,0x0000b400u,0x0000b400u,0x0000b400u}, {0xb4008000u,0xb4008000u,0x34000000u,0x34000000u}, {0x34008000u,0x34008000u,0x34008000u,0x34008000u}, {0x0000b400u,0x0000b400u,0x80003400u,0x80003400u}, {0xb4008000u,0xb4008000u,0xb4008000u,0xb4008000u}, {0x80003400u,0x80003400u,0x0000b400u,0x0000b400u}, {0x00003400u,0x0000b400u,0x00003400u,0x0000b400u}, {0x31a8b1a8u,0xb1a831a8u,0xb1a831a8u,0x31a8b1a8u}, {0xb4008000u,0x34000000u,0xb4008000u,0x34000000u}, {0x31a831a8u,0xb1a8b1a8u,0xb1a8b1a8u,0x31a831a8u}, {0x34008000u,0xb4008000u,0x34008000u,0xb4008000u}, {0xb1a8b1a8u,0x31a831a8u,0x31a831a8u,0xb1a8b1a8u}, {0x80003400u,0x0000b400u,0x80003400u,0x0000b400u}, {0x31a8b1a8u,0xb1a831a8u,0xb1a831a8u,0x31a8b1a8u},
  {0x00003400u,0x00003400u,0x00003400u,0x00003400u}, {0x00003400u,0x00003400u,0x0000b400u,0x0000b400u}, {0x00003400u,0x00003400u,0x00003400u,0x00003400u}, {0x00003400u,0x00003400u,0x0000b400u,0x0000b400u}, {0x34008000u,0x34008000u,0x34008000u,0x34008000u}, {0x34008000u,0x34008000u,0xb4008000u,0xb4008000u}, {0x34008000u,0x34008000u,0x34008000u,0x34008000u}, {0x34008000u,0x34008000u,0xb4008000u,0xb4008000u}, {0x00003400u,0x0000b400u,0x00003400u,0x0000b400u}, {0x31a831a8u,0xb1a8b1a8u,0xb1a8b1a8u,0x31a831a8u}, {0x34000000u,0xb4008000u,0x34000000u,0xb4008000u}, {0x31a8b1a8u,0xb1a831a8u,0xb1a831a8u,0x31a8b1a8u}, {0x34008000u,0xb4008000u,0x34008000u,0xb4008000u}, {0x31a8b1a8u,0xb1a831a8u,0xb1a831a8u,0x31a8b1a8u}, {0x0000b400u,0x80003400u,0x0000b400u,0x80003400u}, {0xb1a8b1a8u,0x31a831a8u,0x31a831a8u,0xb1a8b1a8u}, {0x00003400u,0x00003400u,0x00003400u,0x00003400u}, {0x34000000u,0x34000000u,0xb4008000u,0xb4008000u}, {0x0000b400u,0x0000b400u,0x0000b400u,0x0000b400u}, {0xb4008000u,0xb4008000u,0x34000000u,0x34000000u}, {0x34008000u,0x34008000u,0x34008000u,0x34008000u}, {0x0000b400u,0x0000b400u,0x80003400u,0x80003400u}, {0xb4008000u,0xb4008000u,0xb4008000u,0xb4008000u}, {0x80003400u,0x80003400u,0x0000b400u,0x0000b400u}, {0x00003400u,0x0000b400u,0x00003400u,0x0000b400u}, {0x31a8b1a8u,0xb1a831a8u,0xb1a831a8u,0x31a8b1a8u}, {0xb4008000u,0x34000000u,0xb4008000u,0x34000000u}, {0x31a831a8u,0xb1a8b1a8u,0xb1a8b1a8u,0x31a831a8u}, {0x34008000u,0xb4008000u,0x34008000u,0xb4008000u}, {0xb1a8b1a8u,0x31a831a8u,0x31a831a8u,0xb1a8b1a8u}, {0x80003400u,0x0000b400u,0x80003400u,0x0000b400u}, {0x31a8b1a8u,0xb1a831a8u,0xb1a831a8u,0x31a8b1a8u},
  {0x3f800000u,0x80000000u,0x3f800000u,0x80000000u}, {0x3f800000u,0x80000000u,0x3f800000u,0x80000000u}, {0x3f800000u,0x80000000u,0x3f800000u,0x80000000u}, {0x3f800000u,0x80000000u,0x3f800000u,0x80000000u}, {0x3f800000u,0x80000000u,0x3f7b14beu,0xbe47c5c2u}, {0x3f7fb10fu,0xbd48fb30u,0x3f7853f8u,0xbe78cfccu}, {0x3f7ec46du,0xbdc8bd36u,0x3f74fa0bu,0xbe94a031u}, {0x3f7d3aacu,0xbe164083u,0x3f710908u,0xbeac7cd4u}, {0x3f800000u,0x80000000u,0x3f6c835eu,0xbec3ef15u}, {0x3f7ec46du,0xbdc8bd36u,0x3f61c598u,0xbef15aeau}, {0x3f7b14beu,0xbe47c5c2u,0x3f54db31u,0xbf0e39dau}, {0x3f74fa0bu,0xbe94a031u,0x3f45e403u,0xbf226799u}, {0x3f800000u,0x80000000u,0x3f54db31u,0xbf0e39dau}, {0x3f7d3aacu,0xbe164083u,0x3f3daef9u,0xbf2beb4au}, {0x3f74fa0bu,0xbe94a031u,0x3f226799u,0xbf45e403u}, {0x3f676bd8u,0xbedae880u,0x3f039c3du,0xbf5b941au}, {0x3f800000u,0x80000000u,0x3f3504f3u,0xbf3504f3u}, {0x3f7b14beu,0xbe47c5c2u,0x3f0e39dau,0xbf54db31u}, {0x3f6c835eu,0xbec3ef15u,0x3ec3ef15u,0xbf6c835eu}, {0x3f54db31u,0xbf0e39dau,0x3e47c5c2u,0xbf7b14beu}, {0x3f800000u,0x80000000u,0x3f0e39dau,0xbf54db31u}, {0x3f7853f8u,0xbe78cfccu,0x3eac7cd4u,0xbf710908u}, {0x3f61c598u,0xbef15aeau,0x3dc8bd36u,0xbf7ec46du}, {0x3f3daef9u,0xbf2beb4au,0xbe164083u,0xbf7d3aacu}, {0x3f800000u,0x80000000u,0x3ec3ef15u,0xbf6c835eu}, {0x3f74fa0bu,0xbe94a031u,0x3dc8bd36u,0xbf7ec46du}, {0x3f54db31u,0xbf0e39dau,0xbe47c5c2u,0xbf7b14beu}, {0x3f226799u,0xbf45e403u,0xbef15aeau,0xbf61c598u}, {0x3f800000u,0x80000000u,0x3e47c5c2u,0xbf7b14beu}, {0x3f710908u,0xbeac7cd4u,0xbe164083u,0xbf7d3aacu}, {0x3f45e403u,0xbf226799u,0xbef15aeau,0xbf61c598u}, {0x3f039c3du,0xbf5b941au,0xbf3daef9u,0xbf2beb4au},
  {0x3f800000u,0x80000000u,0x3f800000u,0x80000000u}, {0x3f800000u,0x80000000u,0x3f800000u,0x80000000u}, {0x3f800000u,0x80000000u,0x3f800000u,0x80000000u}, {0x3f800000u,0x80000000u,0x3f800000u,0x80000000u}, {0x3f6c835eu,0xbec3ef15u,0x3f54db31u,0xbf0e39dau}, {0x3f676bd8u,0xbedae880u,0x3f4d9f02u,0xbf187fc0u}, {0x3f61c598u,0xbef15aeau,0x3f45e403u,0xbf226799u}, {0x3f5b941au,0xbf039c3du,0x3f3daef9u,0xbf2beb4au}, {0x3f3504f3u,0xbf3504f3u,0x3ec3ef15u,0xbf6c835eu}, {0x3f226799u,0xbf45e403u,0x3e94a031u,0xbf74fa0bu}, {0x3f0e39dau,0xbf54db31u,0x3e47c5c2u,0xbf7b14beu}, {0x3ef15aeau,0xbf61c598u,0x3dc8bd36u,0xbf7ec46du}, {0x3ec3ef15u,0xbf6c835eu,0xbe47c5c2u,0xbf7b14beu}, {0x3e78cfccu,0xbf7853f8u,0xbeac7cd4u,0xbf710908u}, {0x3dc8bd36u,0xbf7ec46du,0xbef15aeau,0xbf61c598u}, {0xbd48fb30u,0xbf7fb10fu,0xbf187fc0u,0xbf4d9f02u}, {0x248d3132u,0xbf800000u,0xbf3504f3u,0xbf3504f3u}, {0xbe47c5c2u,0xbf7b14beu,0xbf54db31u,0xbf0e39dau}, {0xbec3ef15u,0xbf6c835eu,0xbf6c835eu,0xbec3ef15u}, {0xbf0e39dau,0xbf54db31u,0xbf7b14beu,0xbe47c5c2u}, {0xbec3ef15u,0xbf6c835eu,0xbf7b14beu,0xbe47c5c2u}, {0xbf187fc0u,0xbf4d9f02u,0xbf7fb10fu,0x3d48fb30u}, {0xbf45e403u,0xbf226799u,0xbf74fa0bu,0x3e94a031u}, {0xbf676bd8u,0xbedae880u,0xbf5b941au,0x3f039c3du}, {0xbf3504f3u,0xbf3504f3u,0xbf6c835eu,0x3ec3ef15u}, {0xbf61c598u,0xbef15aeau,0xbf45e403u,0x3f226799u}, {0xbf7b14beu,0xbe47c5c2u,0xbf0e39dau,0x3f54db31u}, {0xbf7ec46du,0x3dc8bd36u,0xbe94a031u,0x3f74fa0bu}, {0xbf6c835eu,0xbec3ef15u,0xbf0e39dau,0x3f54db31u}, {0xbf7fb10fu,0xbd48fb30u,0xbe78cfccu,0x3f7853f8u}, {0xbf74fa0bu,0x3e94a031u,0x3dc8bd36u,0x3f7ec46du}, {0xbf4d9f02u,0x3f187fc0u,0x3edae880u,0x3f676bd8u},
  {0x3f800000u,0x80000000u,0x3f7ec46du,0xbdc8bd36u}, {0x3f7fec43u,0xbcc90ab0u,0x3f7e1324u,0xbdfab273u}, {0x3f7fb10fu,0xbd48fb30u,0x3f7d3aacu,0xbe164083u}, {0x3f7f4e6du,0xbd96a905u,0x3f7c3b28u,0xbe2f10a2u}, {0x3f800000u,0x80000000u,0x3f74fa0bu,0xbe94a031u}, {0x3f7f4e6du,0xbd96a905u,0x3f6ed89eu,0xbeb8442au}, {0x3f7d3aacu,0xbe164083u,0x3f676bd8u,0xbedae880u}, {0x3f79c79du,0xbe605c13u,0x3f5ebe05u,0xbefc5d27u}, {0x3f800000u,0x80000000u,0x3f61c598u,0xbef15aeau}, {0x3f7e1324u,0xbdfab273u,0x3f514d3du,0xbf13682au}, {0x3f7853f8u,0xbe78cfccu,0x3f3daef9u,0xbf2beb4au}, {0x3f6ed89eu,0xbeb8442au,0x3f273656u,0xbf41d870u}, {0x3f800000u,0x80000000u,0x3f45e403u,0xbf226799u}, {0x3f7c3b28u,0xbe2f10a2u,0x3f273656u,0xbf41d870u}, {0x3f710908u,0xbeac7cd4u,0x3f039c3du,0xbf5b941au}, {0x3f5ebe05u,0xbefc5d27u,0x3eb8442au,0xbf6ed89eu}, {0x3f800000u,0x80000000u,0x3f226799u,0xbf45e403u}, {0x3f79c79du,0xbe605c13u,0x3ee63375u,0xbf64aa59u}, {0x3f676bd8u,0xbedae880u,0x3e78cfccu,0xbf7853f8u}, {0x3f49d112u,0xbf1d7fd1u,0x3cc90ab0u,0xbf7fec43u}, {0x3f800000u,0x80000000u,0x3ef15aeau,0xbf61c598u}, {0x3f76ba07u,0xbe888e93u,0x3e605c13u,0xbf79c79du}, {0x3f5b941au,0xbf039c3du,0xbd48fb30u,0xbf7fb10fu}, {0x3f3085bbu,0xbf396842u,0xbea09ae5u,0xbf731447u}, {0x3f800000u,0x80000000u,0x3e94a031u,0xbf74fa0bu}, {0x3f731447u,0xbea09ae5u,0xbcc90ab0u,0xbf7fec43u}, {0x3f4d9f02u,0xbf187fc0u,0xbeac7cd4u,0xbf710908u}, {0x3f13682au,0xbf514d3du,0xbf1d7fd1u,0xbf49d112u}, {0x3f800000u,0x80000000u,0x3dc8bd36u,0xbf7ec46du}, {0x3f6ed89eu,0xbeb8442au,0xbe888e93u,0xbf76ba07u}, {0x3f3daef9u,0xbf2beb4au,0xbf187fc0u,0xbf4d9f02u}, {0x3ee63375u,0xbf64aa59u,0xbf584853u,0xbf08f59bu},
  {0x3f7b14beu,0xbe47c5c2u,0x3f74fa0bu,0xbe94a031u}, {0x3f79c79du,0xbe605c13u,0x3f731447u,0xbea09ae5u}, {0x3f7853f8u,0xbe78cfccu,0x3f710908u,0xbeac7cd4u}, {0x3f76ba07u,0xbe888e93u,0x3f6ed89eu,0xbeb8442au}, {0x3f54db31u,0xbf0e39dau,0x3f226799u,0xbf45e403u}, {0x3f49d112u,0xbf1d7fd1u,0x3f13682au,0xbf514d3du}, {0x3f3daef9u,0xbf2beb4au,0x3f039c3du,0xbf5b941au}, {0x3f3085bbu,0xbf396842u,0x3ee63375u,0xbf64aa59u}, {0x3f0e39dau,0xbf54db31u,0x3dc8bd36u,0xbf7ec46du}, {0x3ee63375u,0xbf64aa59u,0xbcc90ab0u,0xbf7fec43u}, {0x3eac7cd4u,0xbf710908u,0xbe164083u,0xbf7d3aacu}, {0x3e605c13u,0xbf79c79du,0xbe888e93u,0xbf76ba07u}, {0x3e47c5c2u,0xbf7b14beu,0xbef15aeau,0xbf61c598u}, {0x3cc90ab0u,0xbf7fec43u,0xbf1d7fd1u,0xbf49d112u}, {0xbe164083u,0xbf7d3aacu,0xbf3daef9u,0xbf2beb4au}, {0xbea09ae5u,0xbf731447u,0xbf584853u,0xbf08f59bu}, {0xbe47c5c2u,0xbf7b14beu,0xbf61c598u,0xbef15aeau}, {0xbecf7bcau,0xbf6a09a7u,0xbf76ba07u,0xbe888e93u}, {0xbf187fc0u,0xbf4d9f02u,0xbf7fb10fu,0xbd48fb30u}, {0xbf41d870u,0xbf273656u,0xbf7c3b28u,0x3e2f10a2u}, {0xbf0e39dau,0xbf54db31u,0xbf7ec46du,0x3dc8bd36u}, {0xbf41d870u,0xbf273656u,0xbf6ed89eu,0x3eb8442au}, {0xbf676bd8u,0xbedae880u,0xbf4d9f02u,0x3f187fc0u}, {0xbf7c3b28u,0xbe2f10a2u,0xbf1d7fd1u,0x3f49d112u}, {0xbf54db31u,0xbf0e39dau,0xbf45e403u,0x3f226799u}, {0xbf76ba07u,0xbe888e93u,0xbf08f59bu,0x3f584853u}, {0xbf7fb10fu,0x3d48fb30u,0xbe78cfccu,0x3f7853f8u}, {0xbf6ed89eu,0x3eb8442au,0x3d96a905u,0x3f7f4e6du}, {0xbf7b14beu,0xbe47c5c2u,0xbe94a031u,0x3f74fa0bu}, {0xbf7c3b28u,0x3e2f10a2u,0x3d96a905u,0x3f7f4e6du}, {0xbf5b941au,0x3f039c3du,0x3edae880u,0x3f676bd8u}, {0xbf1d7fd1u,0x3f49d112u,0x3f396842u,0x3f3085bbu},
  {0x3f800000u,0x80000000u,0x3f3504f3u,0xbf3504f3u}, {0x3f7b14beu,0xbe47c5c2u,0x3f0e39dau,0xbf54db31u}, {0x3f6c835eu,0xbec3ef15u,0x3ec3ef15u,0xbf6c835eu}, {0x3f54db31u,0xbf0e39dau,0x3e47c5c2u,0xbf7b14beu}, {0x3f7fec43u,0xbcc90ab0u,0x3f3085bbu,0xbf396842u}, {0x3f79c79du,0xbe605c13u,0x3f08f59bu,0xbf584853u}, {0x3f6a09a7u,0xbecf7bcau,0x3eb8442au,0xbf6ed89eu}, {0x3f514d3du,0xbf13682au,0x3e2f10a2u,0xbf7c3b28u}, {0x3f7fb10fu,0xbd48fb30u,0x3f2beb4au,0xbf3daef9u}, {0x3f7853f8u,0xbe78cfccu,0x3f039c3du,0xbf5b941au}, {0x3f676bd8u,0xbedae880u,0x3eac7cd4u,0xbf710908u}, {0x3f4d9f02u,0xbf187fc0u,0x3e164083u,0xbf7d3aacu}, {0x3f7f4e6du,0xbd96a905u,0x3f273656u,0xbf41d870u}, {0x3f76ba07u,0xbe888e93u,0x3efc5d27u,0xbf5ebe05u}, {0x3f64aa59u,0xbee63375u,0x3ea09ae5u,0xbf731447u}, {0x3f49d112u,0xbf1d7fd1u,0x3dfab273u,0xbf7e1324u}, {0x3f7ec46du,0xbdc8bd36u,0x3f226799u,0xbf45e403u}, {0x3f74fa0bu,0xbe94a031u,0x3ef15aeau,0xbf61c598u}, {0x3f61c598u,0xbef15aeau,0x3e94a031u,0xbf74fa0bu}, {0x3f45e403u,0xbf226799u,0x3dc8bd36u,0xbf7ec46du}, {0x3f7e1324u,0xbdfab273u,0x3f1d7fd1u,0xbf49d112u}, {0x3f731447u,0xbea09ae5u,0x3ee63375u,0xbf64aa59u}, {0x3f5ebe05u,0xbefc5d27u,0x3e888e93u,0xbf76ba07u}, {0x3f41d870u,0xbf273656u,0x3d96a905u,0xbf7f4e6du}, {0x3f7d3aacu,0xbe164083u,0x3f187fc0u,0xbf4d9f02u}, {0x3f710908u,0xbeac7cd4u,0x3edae880u,0xbf676bd8u}, {0x3f5b941au,0xbf039c3du,0x3e78cfccu,0xbf7853f8u}, {0x3f3daef9u,0xbf2beb4au,0x3d48fb30u,0xbf7fb10fu}, {0x3f7c3b28u,0xbe2f10a2u,0x3f13682au,0xbf514d3du}, {0x3f6ed89eu,0xbeb8442au,0x3ecf7bcau,0xbf6a09a7u}, {0x3f584853u,0xbf08f59bu,0x3e605c13u,0xbf79c79du}, {0x3f396842u,0xbf3085bbu,0x3cc90ab0u,0xbf7fec43u},
  {0x248d3132u,0xbf800000u,0xbf3504f3u,0xbf3504f3u}, {0xbe47c5c2u,0xbf7b14beu,0xbf54db31u,0xbf0e39dau}, {0xbec3ef15u,0xbf6c835eu,0xbf6c835eu,0xbec3ef15u}, {0xbf0e39dau,0xbf54db31u,0xbf7b14beu,0xbe47c5c2u}, {0xbcc90ab0u,0xbf7fec43u,0xbf396842u,0xbf3085bbu}, {0xbe605c13u,0xbf79c79du,0xbf584853u,0xbf08f59bu}, {0xbecf7bcau,0xbf6a09a7u,0xbf6ed89eu,0xbeb8442au}, {0xbf13682au,0xbf514d3du,0xbf7c3b28u,0xbe2f10a2u}, {0xbd48fb30u,0xbf7fb10fu,0xbf3daef9u,0xbf2beb4au}, {0xbe78cfccu,0xbf7853f8u,0xbf5b941au,0xbf039c3du}, {0xbedae880u,0xbf676bd8u,0xbf710908u,0xbeac7cd4u}, {0xbf187fc0u,0xbf4d9f02u,0xbf7d3aacu,0xbe164083u}, {0xbd96a905u,0xbf7f4e6du,0xbf41d870u,0xbf273656u}, {0xbe888e93u,0xbf76ba07u,0xbf5ebe05u,0xbefc5d27u}, {0xbee63375u,0xbf64aa59u,0xbf731447u,0xbea09ae5u}, {0xbf1d7fd1u,0xbf49d112u,0xbf7e1324u,0xbdfab273u}, {0xbdc8bd36u,0xbf7ec46du,0xbf45e403u,0xbf226799u}, {0xbe94a031u,0xbf74fa0bu,0xbf61c598u,0xbef15aeau}, {0xbef15aeau,0xbf61c598u,0xbf74fa0bu,0xbe94a031u}, {0xbf226799u,0xbf45e403u,0xbf7ec46du,0xbdc8bd36u}, {0xbdfab273u,0xbf7e1324u,0xbf49d112u,0xbf1d7fd1u}, {0xbea09ae5u,0xbf731447u,0xbf64aa59u,0xbee63375u}, {0xbefc5d27u,0xbf5ebe05u,0xbf76ba07u,0xbe888e93u}, {0xbf273656u,0xbf41d870u,0xbf7f4e6du,0xbd96a905u}, {0xbe164083u,0xbf7d3aacu,0xbf4d9f02u,0xbf187fc0u}, {0xbeac7cd4u,0xbf710908u,0xbf676bd8u,0xbedae880u}, {0xbf039c3du,0xbf5b941au,0xbf7853f8u,0xbe78cfccu}, {0xbf2beb4au,0xbf3daef9u,0xbf7fb10fu,0xbd48fb30u}, {0xbe2f10a2u,0xbf7c3b28u,0xbf514d3du,0xbf13682au}, {0xbeb8442au,0xbf6ed89eu,0xbf6a09a7u,0xbecf7bcau}, {0xbf08f59bu,0xbf584853u,0xbf79c79du,0xbe605c13u}, {0xbf3085bbu,0xbf396842u,0xbf7fec43u,0xbcc90ab0u},
  {0x3f7ffb11u,0xbc490e90u,0x3f32c8c9u,0xbf373a23u}, {0x3f7a7302u,0xbe541501u,0x3f0b9a6bu,0xbf5695e5u}, {0x3f6b4b0cu,0xbec9b953u,0x3ebe1d4au,0xbf6db293u}, {0x3f531849u,0xbf10d3cdu,0x3e3b6ecfu,0xbf7baccdu}, {0x3f7fd397u,0xbd16c32cu,0x3f2e3bdeu,0xbf3b8f3bu}, {0x3f791298u,0xbe6c9a7fu,0x3f064b82u,0xbf59f26au}, {0x3f68bf3cu,0xbed53641u,0x3eb263efu,0xbf6ff573u}, {0x3f4f7a1fu,0xbf15f6d9u,0x3e22abb6u,0xbf7cbfc9u}, {0x3f7f84abu,0xbd7b2b74u,0x3f299415u,0xbf3fc767u}, {0x3f778bc5u,0xbe827dc0u,0x3f00e7e4u,0xbf5d2d53u}, {0x3f660f88u,0xbee0924fu,0x3ea68f12u,0xbf721352u}, {0x3f4bbbf8u,0xbf1b02c6u,0x3e09cf86u,0xbf7dabccu}, {0x3f7f0e58u,0xbdafb680u,0x3f24d225u,0xbf43e200u}, {0x3f75dec6u,0xbe8e9a22u,0x3ef6e0cbu,0xbf604621u}, {0x3f633c5au,0xbeebcbbbu,0x3e9aa086u,0xbf740bddu}, {0x3f47de65u,0xbf1ff6cbu,0x3de1bc2eu,0xbf7e70b0u}, {0x3f7e70b0u,0xbde1bc2eu,0x3f1ff6cbu,0xbf47de65u}, {0x3f740bddu,0xbe9aa086u,0x3eebcbbbu,0xbf633c5au}, {0x3f604621u,0xbef6e0cbu,0x3e8e9a22u,0xbf75dec6u}, {0x3f43e200u,0xbf24d225u,0x3dafb680u,0xbf7f0e58u}, {0x3f7dabccu,0xbe09cf86u,0x3f1b02c6u,0xbf4bbbf8u}, {0x3f721352u,0xbea68f12u,0x3ee0924fu,0xbf660f88u}, {0x3f5d2d53u,0xbf00e7e4u,0x3e827dc0u,0xbf778bc5u}, {0x3f3fc767u,0xbf299415u,0x3d7b2b74u,0xbf7f84abu}, {0x3f7cbfc9u,0xbe22abb6u,0x3f15f6d9u,0xbf4f7a1fu}, {0x3f6ff573u,0xbeb263efu,0x3ed53641u,0xbf68bf3cu}, {0x3f59f26au,0xbf064b82u,0x3e6c9a7fu,0xbf791298u}, {0x3f3b8f3bu,0xbf2e3bdeu,0x3d16c32cu,0xbf7fd397u}, {0x3f7baccdu,0xbe3b6ecfu,0x3f10d3cdu,0xbf531849u}, {0x3f6db293u,0xbebe1d4au,0x3ec9b953u,0xbf6b4b0cu}, {0x3f5695e5u,0xbf0b9a6bu,0x3e541501u,0xbf7a7302u}, {0x3f373a23u,0xbf32c8c9u,0x3c490e90u,0xbf7ffb11u},
  {0xbc490e90u,0xbf7ffb11u,0xbf373a23u,0xbf32c8c9u}, {0xbe541501u,0xbf7a7302u,0xbf5695e5u,0xbf0b9a6bu}, {0xbec9b953u,0xbf6b4b0cu,0xbf6db293u,0xbebe1d4au}, {0xbf10d3cdu,0xbf531849u,0xbf7baccdu,0xbe3b6ecfu}, {0xbd16c32cu,0xbf7fd397u,0xbf3b8f3bu,0xbf2e3bdeu}, {0xbe6c9a7fu,0xbf791298u,0xbf59f26au,0xbf064b82u}, {0xbed53641u,0xbf68bf3cu,0xbf6ff573u,0xbeb263efu}, {0xbf15f6d9u,0xbf4f7a1fu,0xbf7cbfc9u,0xbe22abb6u}, {0xbd7b2b74u,0xbf7f84abu,0xbf3fc767u,0xbf299415u}, {0xbe827dc0u,0xbf778bc5u,0xbf5d2d53u,0xbf00e7e4u}, {0xbee0924fu,0xbf660f88u,0xbf721352u,0xbea68f12u}, {0xbf1b02c6u,0xbf4bbbf8u,0xbf7dabccu,0xbe09cf86u}, {0xbdafb680u,0xbf7f0e58u,0xbf43e200u,0xbf24d225u}, {0xbe8e9a22u,0xbf75dec6u,0xbf604621u,0xbef6e0cbu}, {0xbeebcbbbu,0xbf633c5au,0xbf740bddu,0xbe9aa086u}, {0xbf1ff6cbu,0xbf47de65u,0xbf7e70b0u,0xbde1bc2eu}, {0xbde1bc2eu,0xbf7e70b0u,0xbf47de65u,0xbf1ff6cbu}, {0xbe9aa086u,0xbf740bddu,0xbf633c5au,0xbeebcbbbu}, {0xbef6e0cbu,0xbf604621u,0xbf75dec6u,0xbe8e9a22u}, {0xbf24d225u,0xbf43e200u,0xbf7f0e58u,0xbdafb680u}, {0xbe09cf86u,0xbf7dabccu,0xbf4bbbf8u,0xbf1b02c6u}, {0xbea68f12u,0xbf721352u,0xbf660f88u,0xbee0924fu}, {0xbf00e7e4u,0xbf5d2d53u,0xbf778bc5u,0xbe827dc0u}, {0xbf299415u,0xbf3fc767u,0xbf7f84abu,0xbd7b2b74u}, {0xbe22abb6u,0xbf7cbfc9u,0xbf4f7a1fu,0xbf15f6d9u}, {0xbeb263efu,0xbf6ff573u,0xbf68bf3cu,0xbed53641u}, {0xbf064b82u,0xbf59f26au,0xbf791298u,0xbe6c9a7fu}, {0xbf2e3bdeu,0xbf3b8f3bu,0xbf7fd397u,0xbd16c32cu}, {0xbe3b6ecfu,0xbf7baccdu,0xbf531849u,0xbf10d3cdu}, {0xbebe1d4au,0xbf6db293u,0xbf6b4b0cu,0xbec9b953u}, {0xbf0b9a6bu,0xbf5695e5u,0xbf7a7302u,0xbe541501u}, {0xbf32c8c9u,0xbf373a23u,0xbf7ffb11u,0xbc490e90u},
};
__device__ const uint2 c_w2048[2048] = {
  {0x3f800000u,0x00000000u}, {0x3f7fffb1u,0xbb490fc6u}, {0x3f7ffec4u,0xbbc90f88u}, {0x3f7ffd39u,0xbc16cb58u}, {0x3f7ffb11u,0xbc490e90u}, {0x3f7ff84au,0xbc7b514bu}, {0x3f7ff4e6u,0xbc96c9b6u}, {0x3f7ff0e3u,0xbcafea69u},
  {0x3f7fec43u,0xbcc90ab0u}, {0x3f7fe705u,0xbce22a7au}, {0x3f7fe129u,0xbcfb49bau}, {0x3f7fdaafu,0xbd0a342fu}, {0x3f7fd397u,0xbd16c32cu}, {0x3f7fcbe2u,0xbd2351cbu}, {0x3f7fc38fu,0xbd2fe007u}, {0x3f7fba9eu,0xbd3c6dd5u},
  {0x3f7fb10fu,0xbd48fb30u}, {0x3f7fa6e3u,0xbd55880eu}, {0x3f7f9c18u,0xbd621469u}, {0x3f7f90b1u,0xbd6ea038u}, {0x3f7f84abu,0xbd7b2b74u}, {0x3f7f7808u,0xbd83db0au}, {0x3f7f6ac7u,0xbd8a200au}, {0x3f7f5ce9u,0xbd9064b4u},
  {0x3f7f4e6du,0xbd96a905u}, {0x3f7f3f54u,0xbd9cecf9u}, {0x3f7f2f9du,0xbda3308cu}, {0x3f7f1f49u,0xbda973bau}, {0x3f7f0e58u,0xbdafb680u}, {0x3f7efcc9u,0xbdb5f8dau}, {0x3f7eea9du,0xbdbc3ac3u}, {0x3f7ed7d4u,0xbdc27c39u},
  {0x3f7ec46du,0xbdc8bd36u}, {0x3f7eb069u,0xbdcefdb7u}, {0x3f7e9bc9u,0xbdd53db9u}, {0x3f7e868bu,0xbddb7d37u}, {0x3f7e70b0u,0xbde1bc2eu}, {0x3f7e5a38u,0xbde7fa9au}, {0x3f7e4323u,0xbdee3876u}, {0x3f7e2b72u,0xbdf475c0u},
  {0x3f7e1324u,0xbdfab273u}, {0x3f7dfa38u,0xbe007745u}, {0x3f7de0b1u,0xbe039502u}, {0x3f7dc68cu,0xbe06b26eu}, {0x3f7dabccu,0xbe09cf86u}, {0x3f7d906eu,0xbe0cec4au}, {0x3f7d7474u,0xbe1008b7u}, {0x3f7d57deu,0xbe1324cau},
  {0x3f7d3aacu,0xbe164083u}, {0x3f7d1cddu,0xbe195be0u}, {0x3f7cfe73u,0xbe1c76deu}, {0x3f7cdf6cu,0xbe1f917bu}, {0x3f7cbfc9u,0xbe22abb6u}, {0x3f7c9f8au,0xbe25c58cu}, {0x3f7c7eb0u,0xbe28defcu}, {0x3f7c5d3au,0xbe2bf804u},
  {0x3f7c3b28u,0xbe2f10a2u}, {0x3f7c187au,0xbe3228d4u}, {0x3f7bf531u,0xbe354098u}, {0x3f7bd14du,0xbe3857ecu}, {0x3f7baccdu,0xbe3b6ecfu}, {0x3f7b87b2u,0xbe3e853eu}, {0x3f7b61fcu,0xbe419b37u}, {0x3f7b3babu,0xbe44b0b9u},
  {0x3f7b14beu,0xbe47c5c2u}, {0x3f7aed37u,0xbe4ada4fu}, {0x3f7ac516u,0xbe4dee60u}, {0x3f7a9c59u,0xbe5101f1u}, {0x3f7a7302u,0xbe541501u}, {0x3f7a4910u,0xbe57278fu}, {0x3f7a1e84u,0xbe5a3997u}, {0x3f79f35eu,0xbe5d4b1au},
  {0x3f79c79du,0xbe605c13u}, {0x3f799b43u,0xbe636c83u}, {0x3f796e4eu,0xbe667c66u}, {0x3f7940c0u,0xbe698bbau}, {0x3f791298u,0xbe6c9a7fu}, {0x3f78e3d6u,0xbe6fa8b2u}, {0x3f78b47bu,0xbe72b651u}, {0x3f788486u,0xbe75c35au},
  {0x3f7853f8u,0xbe78cfccu}, {0x3f7822d1u,0xbe7bdba4u}, {0x3f77f110u,0xbe7ee6e1u}, {0x3f77beb7u,0xbe80f8c0u}, {0x3f778bc5u,0xbe827dc0u}, {0x3f77583au,0xbe840270u}, {0x3f772417u,0xbe8586ceu}, {0x3f76ef5bu,0xbe870adau},
  {0x3f76ba07u,0xbe888e93u}, {0x3f76841bu,0xbe8a11f7u}, {0x3f764d97u,0xbe8b9507u}, {0x3f76167au,0xbe8d17c0u}, {0x3f75dec6u,0xbe8e9a22u}, {0x3f75a67bu,0xbe901c2cu}, {0x3f756d97u,0xbe919dddu}, {0x3f75341du,0xbe931f35u},
  {0x3f74fa0bu,0xbe94a031u}, {0x3f74bf62u,0xbe9620d2u}, {0x3f748422u,0xbe97a117u}, {0x3f74484bu,0xbe9920feu}, {0x3f740bddu,0xbe9aa086u}, {0x3f73ced9u,0xbe9c1fafu}, {0x3f73913fu,0xbe9d9e78u}, {0x3f73530eu,0xbe9f1cdfu},
  {0x3f731447u,0xbea09ae5u}, {0x3f72d4ebu,0xbea21887u}, {0x3f7294f8u,0xbea395c5u}, {0x3f725470u,0xbea5129fu}, {0x3f721352u,0xbea68f12u}, {0x3f71d19fu,0xbea80b1fu}, {0x3f718f57u,0xbea986c4u}, {0x3f714c7au,0xbeab0201u},
  {0x3f710908u,0xbeac7cd4u}, {0x3f70c501u,0xbeadf73cu}, {0x3f708066u,0xbeaf713au}, {0x3f703b37u,0xbeb0eacbu}, {0x3f6ff573u,0xbeb263efu}, {0x3f6faf1bu,0xbeb3dca5u}, {0x3f6f6830u,0xbeb554ecu}, {0x3f6f20b0u,0xbeb6ccc3u},
  {0x3f6ed89eu,0xbeb8442au}, {0x3f6e8ff8u,0xbeb9bb1eu}, {0x3f6e46beu,0xbebb31a0u}, {0x3f6dfcf2u,0xbebca7afu}, {0x3f6db293u,0xbebe1d4au}, {0x3f6d67a1u,0xbebf926fu}, {0x3f6d1c1du,0xbec1071eu}, {0x3f6cd007u,0xbec27b55u},
  {0x3f6c835eu,0xbec3ef15u}, {0x3f6c3624u,0xbec5625cu}, {0x3f6be858u,0xbec6d529u}, {0x3f6b99fbu,0xbec8477cu}, {0x3f6b4b0cu,0xbec9b953u}, {0x3f6afb8cu,0xbecb2aaeu}, {0x3f6aab7bu,0xbecc9b8bu}, {0x3f6a5ad9u,0xbece0beau},
  {0x3f6a09a7u,0xbecf7bcau}, {0x3f69b7e4u,0xbed0eb2au}, {0x3f696591u,0xbed25a09u}, {0x3f6912aeu,0xbed3c867u}, {0x3f68bf3cu,0xbed53641u}, {0x3f686b39u,0xbed6a399u}, {0x3f6816a8u,0xbed8106bu}, {0x3f67c187u,0xbed97cb9u},
  {0x3f676bd8u,0xbedae880u}, {0x3f671599u,0xbedc53c1u}, {0x3f66beccu,0xbeddbe79u}, {0x3f666771u,0xbedf28a9u}, {0x3f660f88u,0xbee0924fu}, {0x3f65b710u,0xbee1fb6au}, {0x3f655e0bu,0xbee363fau}, {0x3f650479u,0xbee4cbfeu},
  {0x3f64aa59u,0xbee63375u}, {0x3f644facu,0xbee79a5du}, {0x3f63f473u,0xbee900b7u}, {0x3f6398acu,0xbeea6681u}, {0x3f633c5au,0xbeebcbbbu}, {0x3f62df7bu,0xbeed3063u}, {0x3f628210u,0xbeee9479u}, {0x3f62241au,0xbeeff7fbu},
  {0x3f61c598u,0xbef15aeau}, {0x3f61668au,0xbef2bd43u}, {0x3f6106f2u,0xbef41f07u}, {0x3f60a6cfu,0xbef58035u}, {0x3f604621u,0xbef6e0cbu}, {0x3f5fe4e9u,0xbef840c8u}, {0x3f5f8327u,0xbef9a02du}, {0x3f5f20dbu,0xbefafef7u},
  {0x3f5ebe05u,0xbefc5d27u}, {0x3f5e5aa6u,0xbefdbabbu}, {0x3f5df6beu,0xbeff17b2u}, {0x3f5d924du,0xbf003a06u}, {0x3f5d2d53u,0xbf00e7e4u}, {0x3f5cc7d1u,0xbf019573u}, {0x3f5c61c7u,0xbf0242b1u}, {0x3f5bfb34u,0xbf02ef9fu},
  {0x3f5b941au,0xbf039c3du}, {0x3f5b2c79u,0xbf044889u}, {0x3f5ac450u,0xbf04f484u}, {0x3f5a5ba0u,0xbf05a02cu}, {0x3f59f26au,0xbf064b82u}, {0x3f5988adu,0xbf06f686u}, {0x3f591e6au,0xbf07a136u}, {0x3f58b3a1u,0xbf084b92u},
  {0x3f584853u,0xbf08f59bu}, {0x3f57dc7fu,0xbf099f4eu}, {0x3f577026u,0xbf0a48adu}, {0x3f570348u,0xbf0af1b7u}, {0x3f5695e5u,0xbf0b9a6bu}, {0x3f5627feu,0xbf0c42c9u}, {0x3f55b993u,0xbf0cead0u}, {0x3f554aa4u,0xbf0d9281u},
  {0x3f54db31u,0xbf0e39dau}, {0x3f546b3bu,0xbf0ee0dbu}, {0x3f53fac3u,0xbf0f8784u}, {0x3f5389c7u,0xbf102dd5u}, {0x3f531849u,0xbf10d3cdu}, {0x3f52a649u,0xbf11796bu}, {0x3f5233c6u,0xbf121eb0u}, {0x3f51c0c2u,0xbf12c39au},
  {0x3f514d3du,0xbf13682au}, {0x3f50d937u,0xbf140c5fu}, {0x3f5064afu,0xbf14b039u}, {0x3f4fefa8u,0xbf1553b7u}, {0x3f4f7a1fu,0xbf15f6d9u}, {0x3f4f0417u,0xbf16999fu}, {0x3f4e8d90u,0xbf173c07u}, {0x3f4e1689u,0xbf17de12u},
  {0x3f4d9f02u,0xbf187fc0u}, {0x3f4d26fdu,0xbf19210fu}, {0x3f4cae79u,0xbf19c200u}, {0x3f4c3578u,0xbf1a6293u}, {0x3f4bbbf8u,0xbf1b02c6u}, {0x3f4b41fau,0xbf1ba299u}, {0x3f4ac77fu,0xbf1c420cu}, {0x3f4a4c87u,0xbf1ce11fu},
  {0x3f49d112u,0xbf1d7fd1u}, {0x3f495521u,0xbf1e1e22u}, {0x3f48d8b3u,0xbf1ebc12u}, {0x3f485bcau,0xbf1f599fu}, {0x3f47de65u,0xbf1ff6cbu}, {0x3f476085u,0xbf209393u}, {0x3f46e22au,0xbf212ff9u}, {0x3f466354u,0xbf21cbfbu},
  {0x3f45e403u,0xbf226799u}, {0x3f456439u,0xbf2302d3u}, {0x3f44e3f5u,0xbf239da9u}, {0x3f446337u,0xbf24381au}, {0x3f43e200u,0xbf24d225u}, {0x3f436051u,0xbf256bcbu}, {0x3f42de29u,0xbf26050au}, {0x3f425b89u,0xbf269de3u},
  {0x3f41d870u,0xbf273656u}, {0x3f4154e1u,0xbf27ce61u}, {0x3f40d0dau,0xbf286605u}, {0x3f404c5cu,0xbf28fd41u}, {0x3f3fc767u,0xbf299415u}, {0x3f3f41fcu,0xbf2a2a80u}, {0x3f3ebc1bu,0xbf2ac082u}, {0x3f3e35c5u,0xbf2b561bu},
  {0x3f3daef9u,0xbf2beb4au}, {0x3f3d27b8u,0xbf2c800fu}, {0x3f3ca003u,0xbf2d1469u}, {0x3f3c17d9u,0xbf2da859u}, {0x3f3b8f3bu,0xbf2e3bdeu}, {0x3f3b0629u,0xbf2ecef7u}, {0x3f3a7ca4u,0xbf2f61a5u}, {0x3f39f2acu,0xbf2ff3e6u},
  {0x3f396842u,0xbf3085bbu}, {0x3f38dd65u,0xbf311722u}, {0x3f385216u,0xbf31a81du}, {0x3f37c655u,0xbf3238aau}, {0x3f373a23u,0xbf32c8c9u}, {0x3f36ad7fu,0xbf33587au}, {0x3f36206cu,0xbf33e7bcu}, {0x3f3592e7u,0xbf34768fu},
  {0x3f3504f3u,0xbf3504f3u}, {0x3f34768fu,0xbf3592e7u}, {0x3f33e7bcu,0xbf36206cu}, {0x3f33587au,0xbf36ad7fu}, {0x3f32c8c9u,0xbf373a23u}, {0x3f3238aau,0xbf37c655u}, {0x3f31a81du,0xbf385216u}, {0x3f311722u,0xbf38dd65u},
  {0x3f3085bbu,0xbf396842u}, {0x3f2ff3e6u,0xbf39f2acu}, {0x3f2f61a5u,0xbf3a7ca4u}, {0x3f2ecef7u,0xbf3b0629u}, {0x3f2e3bdeu,0xbf3b8f3bu}, {0x3f2da859u,0xbf3c17d9u}, {0x3f2d1469u,0xbf3ca003u}, {0x3f2c800fu,0xbf3d27b8u},
  {0x3f2beb4au,0xbf3daef9u}, {0x3f2b561bu,0xbf3e35c5u}, {0x3f2ac082u,0xbf3ebc1bu}, {0x3f2a2a80u,0xbf3f41fcu}, {0x3f299415u,0xbf3fc767u}, {0x3f28fd41u,0xbf404c5cu}, {0x3f286605u,0xbf40d0dau}, {0x3f27ce61u,0xbf4154e1u},
  {0x3f273656u,0xbf41d870u}, {0x3f269de3u,0xbf425b89u}, {0x3f26050au,0xbf42de29u}, {0x3f256bcbu,0xbf436051u}, {0x3f24d225u,0xbf43e200u}, {0x3f24381au,0xbf446337u}, {0x3f239da9u,0xbf44e3f5u}, {0x3f2302d3u,0xbf456439u},
  {0x3f226799u,0xbf45e403u}, {0x3f21cbfbu,0xbf466354u}, {0x3f212ff9u,0xbf46e22au}, {0x3f209393u,0xbf476085u}, {0x3f1ff6cbu,0xbf47de65u}, {0x3f1f599fu,0xbf485bcau}, {0x3f1ebc12u,0xbf48d8b3u}, {0x3f1e1e22u,0xbf495521u},
  {0x3f1d7fd1u,0xbf49d112u}, {0x3f1ce11fu,0xbf4a4c87u}, {0x3f1c420cu,0xbf4ac77fu}, {0x3f1ba299u,0xbf4b41fau}, {0x3f1b02c6u,0xbf4bbbf8u}, {0x3f1a6293u,0xbf4c3578u}, {0x3f19c200u,0xbf4cae79u}, {0x3f19210fu,0xbf4d26fdu},
  {0x3f187fc0u,0xbf4d9f02u}, {0x3f17de12u,0xbf4e1689u}, {0x3f173c07u,0xbf4e8d90u}, {0x3f16999fu,0xbf4f0417u}, {0x3f15f6d9u,0xbf4f7a1fu}, {0x3f1553b7u,0xbf4fefa8u}, {0x3f14b039u,0xbf5064afu}, {0x3f140c5fu,0xbf50d937u},
  {0x3f13682au,0xbf514d3du}, {0x3f12c39au,0xbf51c0c2u}, {0x3f121eb0u,0xbf5233c6u}, {0x3f11796bu,0xbf52a649u}, {0x3f10d3cdu,0xbf531849u}, {0x3f102dd5u,0xbf5389c7u}, {0x3f0f8784u,0xbf53fac3u}, {0x3f0ee0dbu,0xbf546b3bu},
  {0x3f0e39dau,0xbf54db31u}, {0x3f0d9281u,0xbf554aa4u}, {0x3f0cead0u,0xbf55b993u}, {0x3f0c42c9u,0xbf5627feu}, {0x3f0b9a6bu,0xbf5695e5u}, {0x3f0af1b7u,0xbf570348u}, {0x3f0a48adu,0xbf577026u}, {0x3f099f4eu,0xbf57dc7fu},
  {0x3f08f59bu,0xbf584853u}, {0x3f084b92u,0xbf58b3a1u}, {0x3f07a136u,0xbf591e6au}, {0x3f06f686u,0xbf5988adu}, {0x3f064b82u,0xbf59f26au}, {0x3f05a02cu,0xbf5a5ba0u}, {0x3f04f484u,0xbf5ac450u}, {0x3f044889u,0xbf5b2c79u},
  {0x3f039c3du,0xbf5b941au}, {0x3f02ef9fu,0xbf5bfb34u}, {0x3f0242b1u,0xbf5c61c7u}, {0x3f019573u,0xbf5cc7d1u}, {0x3f00e7e4u,0xbf5d2d53u}, {0x3f003a06u,0xbf5d924du}, {0x3eff17b2u,0xbf5df6beu}, {0x3efdbabbu,0xbf5e5aa6u},
  {0x3efc5d27u,0xbf5ebe05u}, {0x3efafef7u,0xbf5f20dbu}, {0x3ef9a02du,0xbf5f8327u}, {0x3ef840c8u,0xbf5fe4e9u}, {0x3ef6e0cbu,0xbf604621u}, {0x3ef58035u,0xbf60a6cfu}, {0x3ef41f07u,0xbf6106f2u}, {0x3ef2bd43u,0xbf61668au},
  {0x3ef15aeau,0xbf61c598u}, {0x3eeff7fbu,0xbf62241au}, {0x3eee9479u,0xbf628210u}, {0x3eed3063u,0xbf62df7bu}, {0x3eebcbbbu,0xbf633c5au}, {0x3eea6681u,0xbf6398acu}, {0x3ee900b7u,0xbf63f473u}, {0x3ee79a5du,0xbf644facu},
  {0x3ee63375u,0xbf64aa59u}, {0x3ee4cbfeu,0xbf650479u}, {0x3ee363fau,0xbf655e0bu}, {0x3ee1fb6au,0xbf65b710u}, {0x3ee0924fu,0xbf660f88u}, {0x3edf28a9u,0xbf666771u}, {0x3eddbe79u,0xbf66beccu}, {0x3edc53c1u,0xbf671599u},
  {0x3edae880u,0xbf676bd8u}, {0x3ed97cb9u,0xbf67c187u}, {0x3ed8106bu,0xbf6816a8u}, {0x3ed6a399u,0xbf686b39u}, {0x3ed53641u,0xbf68bf3cu}, {0x3ed3c867u,0xbf6912aeu}, {0x3ed25a09u,0xbf696591u}, {0x3ed0eb2au,0xbf69b7e4u},
  {0x3ecf7bcau,0xbf6a09a7u}, {0x3ece0beau,0xbf6a5ad9u}, {0x3ecc9b8bu,0xbf6aab7bu}, {0x3ecb2aaeu,0xbf6afb8cu}, {0x3ec9b953u,0xbf6b4b0cu}, {0x3ec8477cu,0xbf6b99fbu}, {0x3ec6d529u,0xbf6be858u}, {0x3ec5625cu,0xbf6c3624u},
  {0x3ec3ef15u,0xbf6c835eu}, {0x3ec27b55u,0xbf6cd007u}, {0x3ec1071eu,0xbf6d1c1du}, {0x3ebf926fu,0xbf6d67a1u}, {0x3ebe1d4au,0xbf6db293u}, {0x3ebca7afu,0xbf6dfcf2u}, {0x3ebb31a0u,0xbf6e46beu}, {0x3eb9bb1eu,0xbf6e8ff8u},
  {0x3eb8442au,0xbf6ed89eu}, {0x3eb6ccc3u,0xbf6f20b0u}, {0x3eb554ecu,0xbf6f6830u}, {0x3eb3dca5u,0xbf6faf1bu}, {0x3eb263efu,0xbf6ff573u}, {0x3eb0eacbu,0xbf703b37u}, {0x3eaf713au,0xbf708066u}, {0x3eadf73cu,0xbf70c501u},
  {0x3eac7cd4u,0xbf710908u}, {0x3eab0201u,0xbf714c7au}, {0x3ea986c4u,0xbf718f57u}, {0x3ea80b1fu,0xbf71d19fu}, {0x3ea68f12u,0xbf721352u}, {0x3ea5129fu,0xbf725470u}, {0x3ea395c5u,0xbf7294f8u}, {0x3ea21887u,0xbf72d4ebu},
  {0x3ea09ae5u,0xbf731447u}, {0x3e9f1cdfu,0xbf73530eu}, {0x3e9d9e78u,0xbf73913fu}, {0x3e9c1fafu,0xbf73ced9u}, {0x3e9aa086u,0xbf740bddu}, {0x3e9920feu,0xbf74484bu}, {0x3e97a117u,0xbf748422u}, {0x3e9620d2u,0xbf74bf62u},
  {0x3e94a031u,0xbf74fa0bu}, {0x3e931f35u,0xbf75341du}, {0x3e919dddu,0xbf756d97u}, {0x3e901c2cu,0xbf75a67bu}, {0x3e8e9a22u,0xbf75dec6u}, {0x3e8d17c0u,0xbf76167au}, {0x3e8b9507u,0xbf764d97u}, {0x3e8a11f7u,0xbf76841bu},
  {0x3e888e93u,0xbf76ba07u}, {0x3e870adau,0xbf76ef5bu}, {0x3e8586ceu,0xbf772417u}, {0x3e840270u,0xbf77583au}, {0x3e827dc0u,0xbf778bc5u}, {0x3e80f8c0u,0xbf77beb7u}, {0x3e7ee6e1u,0xbf77f110u}, {0x3e7bdba4u,0xbf7822d1u},
  {0x3e78cfccu,0xbf7853f8u}, {0x3e75c35au,0xbf788486u}, {0x3e72b651u,0xbf78b47bu}, {0x3e6fa8b2u,0xbf78e3d6u}, {0x3e6c9a7fu,0xbf791298u}, {0x3e698bbau,0xbf7940c0u}, {0x3e667c66u,0xbf796e4eu}, {0x3e636c83u,0xbf799b43u},
  {0x3e605c13u,0xbf79c79du}, {0x3e5d4b1au,0xbf79f35eu}, {0x3e5a3997u,0xbf7a1e84u}, {0x3e57278fu,0xbf7a4910u}, {0x3e541501u,0xbf7a7302u}, {0x3e5101f1u,0xbf7a9c59u}, {0x3e4dee60u,0xbf7ac516u}, {0x3e4ada4fu,0xbf7aed37u},
  {0x3e47c5c2u,0xbf7b14beu}, {0x3e44b0b9u,0xbf7b3babu}, {0x3e419b37u,0xbf7b61fcu}, {0x3e3e853eu,0xbf7b87b2u}, {0x3e3b6ecfu,0xbf7baccdu}, {0x3e3857ecu,0xbf7bd14du}, {0x3e354098u,0xbf7bf531u}, {0x3e3228d4u,0xbf7c187au},
  {0x3e2f10a2u,0xbf7c3b28u}, {0x3e2bf804u,0xbf7c5d3au}, {0x3e28defcu,0xbf7c7eb0u}, {0x3e25c58cu,0xbf7c9f8au}, {0x3e22abb6u,0xbf7cbfc9u}, {0x3e1f917bu,0xbf7cdf6cu}, {0x3e1c76deu,0xbf7cfe73u}, {0x3e195be0u,0xbf7d1cddu},
  {0x3e164083u,0xbf7d3aacu}, {0x3e1324cau,0xbf7d57deu}, {0x3e1008b7u,0xbf7d7474u}, {0x3e0cec4au,0xbf7d906eu}, {0x3e09cf86u,0xbf7dabccu}, {0x3e06b26eu,0xbf7dc68cu}, {0x3e039502u,0xbf7de0b1u}, {0x3e007745u,0xbf7dfa38u},
  {0x3dfab273u,0xbf7e1324u}, {0x3df475c0u,0xbf7e2b72u}, {0x3dee3876u,0xbf7e4323u}, {0x3de7fa9au,0xbf7e5a38u}, {0x3de1bc2eu,0xbf7e70b0u}, {0x3ddb7d37u,0xbf7e868bu}, {0x3dd53db9u,0xbf7e9bc9u}, {0x3dcefdb7u,0xbf7eb069u},
  {0x3dc8bd36u,0xbf7ec46du}, {0x3dc27c39u,0xbf7ed7d4u}, {0x3dbc3ac3u,0xbf7eea9du}, {0x3db5f8dau,0xbf7efcc9u}, {0x3dafb680u,0xbf7f0e58u}, {0x3da973bau,0xbf7f1f49u}, {0x3da3308cu,0xbf7f2f9du}, {0x3d9cecf9u,0xbf7f3f54u},
  {0x3d96a905u,0xbf7f4e6du}, {0x3d9064b4u,0xbf7f5ce9u}, {0x3d8a200au,0xbf7f6ac7u}, {0x3d83db0au,0xbf7f7808u}, {0x3d7b2b74u,0xbf7f84abu}, {0x3d6ea038u,0xbf7f90b1u}, {0x3d621469u,0xbf7f9c18u}, {0x3d55880eu,0xbf7fa6e3u},
  {0x3d48fb30u,0xbf7fb10fu}, {0x3d3c6dd5u,0xbf7fba9eu}, {0x3d2fe007u,0xbf7fc38fu}, {0x3d2351cbu,0xbf7fcbe2u}, {0x3d16c32cu,0xbf7fd397u}, {0x3d0a342fu,0xbf7fdaafu}, {0x3cfb49bau,0xbf7fe129u}, {0x3ce22a7au,0xbf7fe705u},
  {0x3cc90ab0u,0xbf7fec43u}, {0x3cafea69u,0xbf7ff0e3u}, {0x3c96c9b6u,0xbf7ff4e6u}, {0x3c7b514bu,0xbf7ff84au}, {0x3c490e90u,0xbf7ffb11u}, {0x3c16cb58u,0xbf7ffd39u}, {0x3bc90f88u,0xbf7ffec4u}, {0x3b490fc6u,0xbf7fffb1u},
  {0x00000000u,0xbf800000u}, {0xbb490fc6u,0xbf7fffb1u}, {0xbbc90f88u,0xbf7ffec4u}, {0xbc16cb58u,0xbf7ffd39u}, {0xbc490e90u,0xbf7ffb11u}, {0xbc7b514bu,0xbf7ff84au}, {0xbc96c9b6u,0xbf7ff4e6u}, {0xbcafea69u,0xbf7ff0e3u},
  {0xbcc90ab0u,0xbf7fec43u}, {0xbce22a7au,0xbf7fe705u}, {0xbcfb49bau,0xbf7fe129u}, {0xbd0a342fu,0xbf7fdaafu}, {0xbd16c32cu,0xbf7fd397u}, {0xbd2351cbu,0xbf7fcbe2u}, {0xbd2fe007u,0xbf7fc38fu}, {0xbd3c6dd5u,0xbf7fba9eu},
  {0xbd48fb30u,0xbf7fb10fu}, {0xbd55880eu,0xbf7fa6e3u}, {0xbd621469u,0xbf7f9c18u}, {0xbd6ea038u,0xbf7f90b1u}, {0xbd7b2b74u,0xbf7f84abu}, {0xbd83db0au,0xbf7f7808u}, {0xbd8a200au,0xbf7f6ac7u}, {0xbd9064b4u,0xbf7f5ce9u},
  {0xbd96a905u,0xbf7f4e6du}, {0xbd9cecf9u,0xbf7f3f54u}, {0xbda3308cu,0xbf7f2f9du}, {0xbda973bau,0xbf7f1f49u}, {0xbdafb680u,0xbf7f0e58u}, {0xbdb5f8dau,0xbf7efcc9u}, {0xbdbc3ac3u,0xbf7eea9du}, {0xbdc27c39u,0xbf7ed7d4u},
  {0xbdc8bd36u,0xbf7ec46du}, {0xbdcefdb7u,0xbf7eb069u}, {0xbdd53db9u,0xbf7e9bc9u}, {0xbddb7d37u,0xbf7e868bu}, {0xbde1bc2eu,0xbf7e70b0u}, {0xbde7fa9au,0xbf7e5a38u}, {0xbdee3876u,0xbf7e4323u}, {0xbdf475c0u,0xbf7e2b72u},
  {0xbdfab273u,0xbf7e1324u}, {0xbe007745u,0xbf7dfa38u}, {0xbe039502u,0xbf7de0b1u}, {0xbe06b26eu,0xbf7dc68cu}, {0xbe09cf86u,0xbf7dabccu}, {0xbe0cec4au,0xbf7d906eu}, {0xbe1008b7u,0xbf7d7474u}, {0xbe1324cau,0xbf7d57deu},
  {0xbe164083u,0xbf7d3aacu}, {0xbe195be0u,0xbf7d1cddu}, {0xbe1c76deu,0xbf7cfe73u}, {0xbe1f917bu,0xbf7cdf6cu}, {0xbe22abb6u,0xbf7cbfc9u}, {0xbe25c58cu,0xbf7c9f8au}, {0xbe28defcu,0xbf7c7eb0u}, {0xbe2bf804u,0xbf7c5d3au},
  {0xbe2f10a2u,0xbf7c3b28u}, {0xbe3228d4u,0xbf7c187au}, {0xbe354098u,0xbf7bf531u}, {0xbe3857ecu,0xbf7bd14du}, {0xbe3b6ecfu,0xbf7baccdu}, {0xbe3e853eu,0xbf7b87b2u}, {0xbe419b37u,0xbf7b61fcu}, {0xbe44b0b9u,0xbf7b3babu},
  {0xbe47c5c2u,0xbf7b14beu}, {0xbe4ada4fu,0xbf7aed37u}, {0xbe4dee60u,0xbf7ac516u}, {0xbe5101f1u,0xbf7a9c59u}, {0xbe541501u,0xbf7a7302u}, {0xbe57278fu,0xbf7a4910u}, {0xbe5a3997u,0xbf7a1e84u}, {0xbe5d4b1au,0xbf79f35eu},
  {0xbe605c13u,0xbf79c79du}, {0xbe636c83u,0xbf799b43u}, {0xbe667c66u,0xbf796e4eu}, {0xbe698bbau,0xbf7940c0u}, {0xbe6c9a7fu,0xbf791298u}, {0xbe6fa8b2u,0xbf78e3d6u}, {0xbe72b651u,0xbf78b47bu}, {0xbe75c35au,0xbf788486u},
  {0xbe78cfccu,0xbf7853f8u}, {0xbe7bdba4u,0xbf7822d1u}, {0xbe7ee6e1u,0xbf77f110u}, {0xbe80f8c0u,0xbf77beb7u}, {0xbe827dc0u,0xbf778bc5u}, {0xbe840270u,0xbf77583au}, {0xbe8586ceu,0xbf772417u}, {0xbe870adau,0xbf76ef5bu},
  {0xbe888e93u,0xbf76ba07u}, {0xbe8a11f7u,0xbf76841bu}, {0xbe8b9507u,0xbf764d97u}, {0xbe8d17c0u,0xbf76167au}, {0xbe8e9a22u,0xbf75dec6u}, {0xbe901c2cu,0xbf75a67bu}, {0xbe919dddu,0xbf756d97u}, {0xbe931f35u,0xbf75341du},
  {0xbe94a031u,0xbf74fa0bu}, {0xbe9620d2u,0xbf74bf62u}, {0xbe97a117u,0xbf748422u}, {0xbe9920feu,0xbf74484bu}, {0xbe9aa086u,0xbf740bddu}, {0xbe9c1fafu,0xbf73ced9u}, {0xbe9d9e78u,0xbf73913fu}, {0xbe9f1cdfu,0xbf73530eu},
  {0xbea09ae5u,0xbf731447u}, {0xbea21887u,0xbf72d4ebu}, {0xbea395c5u,0xbf7294f8u}, {0xbea5129fu,0xbf725470u}, {0xbea68f12u,0xbf721352u}, {0xbea80b1fu,0xbf71d19fu}, {0xbea986c4u,0xbf718f57u}, {0xbeab0201u,0xbf714c7au},
  {0xbeac7cd4u,0xbf710908u}, {0xbeadf73cu,0xbf70c501u}, {0xbeaf713au,0xbf708066u}, {0xbeb0eacbu,0xbf703b37u}, {0xbeb263efu,0xbf6ff573u}, {0xbeb3dca5u,0xbf6faf1bu}, {0xbeb554ecu,0xbf6f6830u}, {0xbeb6ccc3u,0xbf6f20b0u},
  {0xbeb8442au,0xbf6ed89eu}, {0xbeb9bb1eu,0xbf6e8ff8u}, {0xbebb31a0u,0xbf6e46beu}, {0xbebca7afu,0xbf6dfcf2u}, {0xbebe1d4au,0xbf6db293u}, {0xbebf926fu,0xbf6d67a1u}, {0xbec1071eu,0xbf6d1c1du}, {0xbec27b55u,0xbf6cd007u},
  {0xbec3ef15u,0xbf6c835eu}, {0xbec5625cu,0xbf6c3624u}, {0xbec6d529u,0xbf6be858u}, {0xbec8477cu,0xbf6b99fbu}, {0xbec9b953u,0xbf6b4b0cu}, {0xbecb2aaeu,0xbf6afb8cu}, {0xbecc9b8bu,0xbf6aab7bu}, {0xbece0beau,0xbf6a5ad9u},
  {0xbecf7bcau,0xbf6a09a7u}, {0xbed0eb2au,0xbf69b7e4u}, {0xbed25a09u,0xbf696591u}, {0xbed3c867u,0xbf6912aeu}, {0xbed53641u,0xbf68bf3cu}, {0xbed6a399u,0xbf686b39u}, {0xbed8106bu,0xbf6816a8u}, {0xbed97cb9u,0xbf67c187u},
  {0xbedae880u,0xbf676bd8u}, {0xbedc53c1u,0xbf671599u}, {0xbeddbe79u,0xbf66beccu}, {0xbedf28a9u,0xbf666771u}, {0xbee0924fu,0xbf660f88u}, {0xbee1fb6au,0xbf65b710u}, {0xbee363fau,0xbf655e0bu}, {0xbee4cbfeu,0xbf650479u},
  {0xbee63375u,0xbf64aa59u}, {0xbee79a5du,0xbf644facu}, {0xbee900b7u,0xbf63f473u}, {0xbeea6681u,0xbf6398acu}, {0xbeebcbbbu,0xbf633c5au}, {0xbeed3063u,0xbf62df7bu}, {0xbeee9479u,0xbf628210u}, {0xbeeff7fbu,0xbf62241au},
  {0xbef15aeau,0xbf61c598u}, {0xbef2bd43u,0xbf61668au}, {0xbef41f07u,0xbf6106f2u}, {0xbef58035u,0xbf60a6cfu}, {0xbef6e0cbu,0xbf604621u}, {0xbef840c8u,0xbf5fe4e9u}, {0xbef9a02du,0xbf5f8327u}, {0xbefafef7u,0xbf5f20dbu},
  {0xbefc5d27u,0xbf5ebe05u}, {0xbefdbabbu,0xbf5e5aa6u}, {0xbeff17b2u,0xbf5df6beu}, {0xbf003a06u,0xbf5d924du}, {0xbf00e7e4u,0xbf5d2d53u}, {0xbf019573u,0xbf5cc7d1u}, {0xbf0242b1u,0xbf5c61c7u}, {0xbf02ef9fu,0xbf5bfb34u},
  {0xbf039c3du,0xbf5b941au}, {0xbf044889u,0xbf5b2c79u}, {0xbf04f484u,0xbf5ac450u}, {0xbf05a02cu,0xbf5a5ba0u}, {0xbf064b82u,0xbf59f26au}, {0xbf06f686u,0xbf5988adu}, {0xbf07a136u,0xbf591e6au}, {0xbf084b92u,0xbf58b3a1u},
  {0xbf08f59bu,0xbf584853u}, {0xbf099f4eu,0xbf57dc7fu}, {0xbf0a48adu,0xbf577026u}, {0xbf0af1b7u,0xbf570348u}, {0xbf0b9a6bu,0xbf5695e5u}, {0xbf0c42c9u,0xbf5627feu}, {0xbf0cead0u,0xbf55b993u}, {0xbf0d9281u,0xbf554aa4u},
  {0xbf0e39dau,0xbf54db31u}, {0xbf0ee0dbu,0xbf546b3bu}, {0xbf0f8784u,0xbf53fac3u}, {0xbf102dd5u,0xbf5389c7u}, {0xbf10d3cdu,0xbf531849u}, {0xbf11796bu,0xbf52a649u}, {0xbf121eb0u,0xbf5233c6u}, {0xbf12c39au,0xbf51c0c2u},
  {0xbf13682au,0xbf514d3du}, {0xbf140c5fu,0xbf50d937u}, {0xbf14b039u,0xbf5064afu}, {0xbf1553b7u,0xbf4fefa8u}, {0xbf15f6d9u,0xbf4f7a1fu}, {0xbf16999fu,0xbf4f0417u}, {0xbf173c07u,0xbf4e8d90u}, {0xbf17de12u,0xbf4e1689u},
  {0xbf187fc0u,0xbf4d9f02u}, {0xbf19210fu,0xbf4d26fdu}, {0xbf19c200u,0xbf4cae79u}, {0xbf1a6293u,0xbf4c3578u}, {0xbf1b02c6u,0xbf4bbbf8u}, {0xbf1ba299u,0xbf4b41fau}, {0xbf1c420cu,0xbf4ac77fu}, {0xbf1ce11fu,0xbf4a4c87u},
  {0xbf1d7fd1u,0xbf49d112u}, {0xbf1e1e22u,0xbf495521u}, {0xbf1ebc12u,0xbf48d8b3u}, {0xbf1f599fu,0xbf485bcau}, {0xbf1ff6cbu,0xbf47de65u}, {0xbf209393u,0xbf476085u}, {0xbf212ff9u,0xbf46e22au}, {0xbf21cbfbu,0xbf466354u},
  {0xbf226799u,0xbf45e403u}, {0xbf2302d3u,0xbf456439u}, {0xbf239da9u,0xbf44e3f5u}, {0xbf24381au,0xbf446337u}, {0xbf24d225u,0xbf43e200u}, {0xbf256bcbu,0xbf436051u}, {0xbf26050au,0xbf42de29u}, {0xbf269de3u,0xbf425b89u},
  {0xbf273656u,0xbf41d870u}, {0xbf27ce61u,0xbf4154e1u}, {0xbf286605u,0xbf40d0dau}, {0xbf28fd41u,0xbf404c5cu}, {0xbf299415u,0xbf3fc767u}, {0xbf2a2a80u,0xbf3f41fcu}, {0xbf2ac082u,0xbf3ebc1bu}, {0xbf2b561bu,0xbf3e35c5u},
  {0xbf2beb4au,0xbf3daef9u}, {0xbf2c800fu,0xbf3d27b8u}, {0xbf2d1469u,0xbf3ca003u}, {0xbf2da859u,0xbf3c17d9u}, {0xbf2e3bdeu,0xbf3b8f3bu}, {0xbf2ecef7u,0xbf3b0629u}, {0xbf2f61a5u,0xbf3a7ca4u}, {0xbf2ff3e6u,0xbf39f2acu},
  {0xbf3085bbu,0xbf396842u}, {0xbf311722u,0xbf38dd65u}, {0xbf31a81du,0xbf385216u}, {0xbf3238aau,0xbf37c655u}, {0xbf32c8c9u,0xbf373a23u}, {0xbf33587au,0xbf36ad7fu}, {0xbf33e7bcu,0xbf36206cu}, {0xbf34768fu,0xbf3592e7u},
  {0xbf3504f3u,0xbf3504f3u}, {0xbf3592e7u,0xbf34768fu}, {0xbf36206cu,0xbf33e7bcu}, {0xbf36ad7fu,0xbf33587au}, {0xbf373a23u,0xbf32c8c9u}, {0xbf37c655u,0xbf3238aau}, {0xbf385216u,0xbf31a81du}, {0xbf38dd65u,0xbf311722u},
  {0xbf396842u,0xbf3085bbu}, {0xbf39f2acu,0xbf2ff3e6u}, {0xbf3a7ca4u,0xbf2f61a5u}, {0xbf3b0629u,0xbf2ecef7u}, {0xbf3b8f3bu,0xbf2e3bdeu}, {0xbf3c17d9u,0xbf2da859u}, {0xbf3ca003u,0xbf2d1469u}, {0xbf3d27b8u,0xbf2c800fu},
  {0xbf3daef9u,0xbf2beb4au}, {0xbf3e35c5u,0xbf2b561bu}, {0xbf3ebc1bu,0xbf2ac082u}, {0xbf3f41fcu,0xbf2a2a80u}, {0xbf3fc767u,0xbf299415u}, {0xbf404c5cu,0xbf28fd41u}, {0xbf40d0dau,0xbf286605u}, {0xbf4154e1u,0xbf27ce61u},
  {0xbf41d870u,0xbf273656u}, {0xbf425b89u,0xbf269de3u}, {0xbf42de29u,0xbf26050au}, {0xbf436051u,0xbf256bcbu}, {0xbf43e200u,0xbf24d225u}, {0xbf446337u,0xbf24381au}, {0xbf44e3f5u,0xbf239da9u}, {0xbf456439u,0xbf2302d3u},
  {0xbf45e403u,0xbf226799u}, {0xbf466354u,0xbf21cbfbu}, {0xbf46e22au,0xbf212ff9u}, {0xbf476085u,0xbf209393u}, {0xbf47de65u,0xbf1ff6cbu}, {0xbf485bcau,0xbf1f599fu}, {0xbf48d8b3u,0xbf1ebc12u}, {0xbf495521u,0xbf1e1e22u},
  {0xbf49d112u,0xbf1d7fd1u}, {0xbf4a4c87u,0xbf1ce11fu}, {0xbf4ac77fu,0xbf1c420cu}, {0xbf4b41fau,0xbf1ba299u}, {0xbf4bbbf8u,0xbf1b02c6u}, {0xbf4c3578u,0xbf1a6293u}, {0xbf4cae79u,0xbf19c200u}, {0xbf4d26fdu,0xbf19210fu},
  {0xbf4d9f02u,0xbf187fc0u}, {0xbf4e1689u,0xbf17de12u}, {0xbf4e8d90u,0xbf173c07u}, {0xbf4f0417u,0xbf16999fu}, {0xbf4f7a1fu,0xbf15f6d9u}, {0xbf4fefa8u,0xbf1553b7u}, {0xbf5064afu,0xbf14b039u}, {0xbf50d937u,0xbf140c5fu},
  {0xbf514d3du,0xbf13682au}, {0xbf51c0c2u,0xbf12c39au}, {0xbf5233c6u,0xbf121eb0u}, {0xbf52a649u,0xbf11796bu}, {0xbf531849u,0xbf10d3cdu}, {0xbf5389c7u,0xbf102dd5u}, {0xbf53fac3u,0xbf0f8784u}, {0xbf546b3bu,0xbf0ee0dbu},
  {0xbf54db31u,0xbf0e39dau}, {0xbf554aa4u,0xbf0d9281u}, {0xbf55b993u,0xbf0cead0u}, {0xbf5627feu,0xbf0c42c9u}, {0xbf5695e5u,0xbf0b9a6bu}, {0xbf570348u,0xbf0af1b7u}, {0xbf577026u,0xbf0a48adu}, {0xbf57dc7fu,0xbf099f4eu},
  {0xbf584853u,0xbf08f59bu}, {0xbf58b3a1u,0xbf084b92u}, {0xbf591e6au,0xbf07a136u}, {0xbf5988adu,0xbf06f686u}, {0xbf59f26au,0xbf064b82u}, {0xbf5a5ba0u,0xbf05a02cu}, {0xbf5ac450u,0xbf04f484u}, {0xbf5b2c79u,0xbf044889u},
  {0xbf5b941au,0xbf039c3du}, {0xbf5bfb34u,0xbf02ef9fu}, {0xbf5c61c7u,0xbf0242b1u}, {0xbf5cc7d1u,0xbf019573u}, {0xbf5d2d53u,0xbf00e7e4u}, {0xbf5d924du,0xbf003a06u}, {0xbf5df6beu,0xbeff17b2u}, {0xbf5e5aa6u,0xbefdbabbu},
  {0xbf5ebe05u,0xbefc5d27u}, {0xbf5f20dbu,0xbefafef7u}, {0xbf5f8327u,0xbef9a02du}, {0xbf5fe4e9u,0xbef840c8u}, {0xbf604621u,0xbef6e0cbu}, {0xbf60a6cfu,0xbef58035u}, {0xbf6106f2u,0xbef41f07u}, {0xbf61668au,0xbef2bd43u},
  {0xbf61c598u,0xbef15aeau}, {0xbf62241au,0xbeeff7fbu}, {0xbf628210u,0xbeee9479u}, {0xbf62df7bu,0xbeed3063u}, {0xbf633c5au,0xbeebcbbbu}, {0xbf6398acu,0xbeea6681u}, {0xbf63f473u,0xbee900b7u}, {0xbf644facu,0xbee79a5du},
  {0xbf64aa59u,0xbee63375u}, {0xbf650479u,0xbee4cbfeu}, {0xbf655e0bu,0xbee363fau}, {0xbf65b710u,0xbee1fb6au}, {0xbf660f88u,0xbee0924fu}, {0xbf666771u,0xbedf28a9u}, {0xbf66beccu,0xbeddbe79u}, {0xbf671599u,0xbedc53c1u},
  {0xbf676bd8u,0xbedae880u}, {0xbf67c187u,0xbed97cb9u}, {0xbf6816a8u,0xbed8106bu}, {0xbf686b39u,0xbed6a399u}, {0xbf68bf3cu,0xbed53641u}, {0xbf6912aeu,0xbed3c867u}, {0xbf696591u,0xbed25a09u}, {0xbf69b7e4u,0xbed0eb2au},
  {0xbf6a09a7u,0xbecf7bcau}, {0xbf6a5ad9u,0xbece0beau}, {0xbf6aab7bu,0xbecc9b8bu}, {0xbf6afb8cu,0xbecb2aaeu}, {0xbf6b4b0cu,0xbec9b953u}, {0xbf6b99fbu,0xbec8477cu}, {0xbf6be858u,0xbec6d529u}, {0xbf6c3624u,0xbec5625cu},
  {0xbf6c835eu,0xbec3ef15u}, {0xbf6cd007u,0xbec27b55u}, {0xbf6d1c1du,0xbec1071eu}, {0xbf6d67a1u,0xbebf926fu}, {0xbf6db293u,0xbebe1d4au}, {0xbf6dfcf2u,0xbebca7afu}, {0xbf6e46beu,0xbebb31a0u}, {0xbf6e8ff8u,0xbeb9bb1eu},
  {0xbf6ed89eu,0xbeb8442au}, {0xbf6f20b0u,0xbeb6ccc3u}, {0xbf6f6830u,0xbeb554ecu}, {0xbf6faf1bu,0xbeb3dca5u}, {0xbf6ff573u,0xbeb263efu}, {0xbf703b37u,0xbeb0eacbu}, {0xbf708066u,0xbeaf713au}, {0xbf70c501u,0xbeadf73cu},
  {0xbf710908u,0xbeac7cd4u}, {0xbf714c7au,0xbeab0201u}, {0xbf718f57u,0xbea986c4u}, {0xbf71d19fu,0xbea80b1fu}, {0xbf721352u,0xbea68f12u}, {0xbf725470u,0xbea5129fu}, {0xbf7294f8u,0xbea395c5u}, {0xbf72d4ebu,0xbea21887u},
  {0xbf731447u,0xbea09ae5u}, {0xbf73530eu,0xbe9f1cdfu}, {0xbf73913fu,0xbe9d9e78u}, {0xbf73ced9u,0xbe9c1fafu}, {0xbf740bddu,0xbe9aa086u}, {0xbf74484bu,0xbe9920feu}, {0xbf748422u,0xbe97a117u}, {0xbf74bf62u,0xbe9620d2u},
  {0xbf74fa0bu,0xbe94a031u}, {0xbf75341du,0xbe931f35u}, {0xbf756d97u,0xbe919dddu}, {0xbf75a67bu,0xbe901c2cu}, {0xbf75dec6u,0xbe8e9a22u}, {0xbf76167au,0xbe8d17c0u}, {0xbf764d97u,0xbe8b9507u}, {0xbf76841bu,0xbe8a11f7u},
  {0xbf76ba07u,0xbe888e93u}, {0xbf76ef5bu,0xbe870adau}, {0xbf772417u,0xbe8586ceu}, {0xbf77583au,0xbe840270u}, {0xbf778bc5u,0xbe827dc0u}, {0xbf77beb7u,0xbe80f8c0u}, {0xbf77f110u,0xbe7ee6e1u}, {0xbf7822d1u,0xbe7bdba4u},
  {0xbf7853f8u,0xbe78cfccu}, {0xbf788486u,0xbe75c35au}, {0xbf78b47bu,0xbe72b651u}, {0xbf78e3d6u,0xbe6fa8b2u}, {0xbf791298u,0xbe6c9a7fu}, {0xbf7940c0u,0xbe698bbau}, {0xbf796e4eu,0xbe667c66u}, {0xbf799b43u,0xbe636c83u},
  {0xbf79c79du,0xbe605c13u}, {0xbf79f35eu,0xbe5d4b1au}, {0xbf7a1e84u,0xbe5a3997u}, {0xbf7a4910u,0xbe57278fu}, {0xbf7a7302u,0xbe541501u}, {0xbf7a9c59u,0xbe5101f1u}, {0xbf7ac516u,0xbe4dee60u}, {0xbf7aed37u,0xbe4ada4fu},
  {0xbf7b14beu,0xbe47c5c2u}, {0xbf7b3babu,0xbe44b0b9u}, {0xbf7b61fcu,0xbe419b37u}, {0xbf7b87b2u,0xbe3e853eu}, {0xbf7baccdu,0xbe3b6ecfu}, {0xbf7bd14du,0xbe3857ecu}, {0xbf7bf531u,0xbe354098u}, {0xbf7c187au,0xbe3228d4u},
  {0xbf7c3b28u,0xbe2f10a2u}, {0xbf7c5d3au,0xbe2bf804u}, {0xbf7c7eb0u,0xbe28defcu}, {0xbf7c9f8au,0xbe25c58cu}, {0xbf7cbfc9u,0xbe22abb6u}, {0xbf7cdf6cu,0xbe1f917bu}, {0xbf7cfe73u,0xbe1c76deu}, {0xbf7d1cddu,0xbe195be0u},
  {0xbf7d3aacu,0xbe164083u}, {0xbf7d57deu,0xbe1324cau}, {0xbf7d7474u,0xbe1008b7u}, {0xbf7d906eu,0xbe0cec4au}, {0xbf7dabccu,0xbe09cf86u}, {0xbf7dc68cu,0xbe06b26eu}, {0xbf7de0b1u,0xbe039502u}, {0xbf7dfa38u,0xbe007745u},
  {0xbf7e1324u,0xbdfab273u}, {0xbf7e2b72u,0xbdf475c0u}, {0xbf7e4323u,0xbdee3876u}, {0xbf7e5a38u,0xbde7fa9au}, {0xbf7e70b0u,0xbde1bc2eu}, {0xbf7e868bu,0xbddb7d37u}, {0xbf7e9bc9u,0xbdd53db9u}, {0xbf7eb069u,0xbdcefdb7u},
  {0xbf7ec46du,0xbdc8bd36u}, {0xbf7ed7d4u,0xbdc27c39u}, {0xbf7eea9du,0xbdbc3ac3u}, {0xbf7efcc9u,0xbdb5f8dau}, {0xbf7f0e58u,0xbdafb680u}, {0xbf7f1f49u,0xbda973bau}, {0xbf7f2f9du,0xbda3308cu}, {0xbf7f3f54u,0xbd9cecf9u},
  {0xbf7f4e6du,0xbd96a905u}, {0xbf7f5ce9u,0xbd9064b4u}, {0xbf7f6ac7u,0xbd8a200au}, {0xbf7f7808u,0xbd83db0au}, {0xbf7f84abu,0xbd7b2b74u}, {0xbf7f90b1u,0xbd6ea038u}, {0xbf7f9c18u,0xbd621469u}, {0xbf7fa6e3u,0xbd55880eu},
  {0xbf7fb10fu,0xbd48fb30u}, {0xbf7fba9eu,0xbd3c6dd5u}, {0xbf7fc38fu,0xbd2fe007u}, {0xbf7fcbe2u,0xbd2351cbu}, {0xbf7fd397u,0xbd16c32cu}, {0xbf7fdaafu,0xbd0a342fu}, {0xbf7fe129u,0xbcfb49bau}, {0xbf7fe705u,0xbce22a7au},
  {0xbf7fec43u,0xbcc90ab0u}, {0xbf7ff0e3u,0xbcafea69u}, {0xbf7ff4e6u,0xbc96c9b6u}, {0xbf7ff84au,0xbc7b514bu}, {0xbf7ffb11u,0xbc490e90u}, {0xbf7ffd39u,0xbc16cb58u}, {0xbf7ffec4u,0xbbc90f88u}, {0xbf7fffb1u,0xbb490fc6u},
  {0xbf800000u,0x00000000u}, {0xbf7fffb1u,0x3b490fc6u}, {0xbf7ffec4u,0x3bc90f88u}, {0xbf7ffd39u,0x3c16cb58u}, {0xbf7ffb11u,0x3c490e90u}, {0xbf7ff84au,0x3c7b514bu}, {0xbf7ff4e6u,0x3c96c9b6u}, {0xbf7ff0e3u,0x3cafea69u},
  {0xbf7fec43u,0x3cc90ab0u}, {0xbf7fe705u,0x3ce22a7au}, {0xbf7fe129u,0x3cfb49bau}, {0xbf7fdaafu,0x3d0a342fu}, {0xbf7fd397u,0x3d16c32cu}, {0xbf7fcbe2u,0x3d2351cbu}, {0xbf7fc38fu,0x3d2fe007u}, {0xbf7fba9eu,0x3d3c6dd5u},
  {0xbf7fb10fu,0x3d48fb30u}, {0xbf7fa6e3u,0x3d55880eu}, {0xbf7f9c18u,0x3d621469u}, {0xbf7f90b1u,0x3d6ea038u}, {0xbf7f84abu,0x3d7b2b74u}, {0xbf7f7808u,0x3d83db0au}, {0xbf7f6ac7u,0x3d8a200au}, {0xbf7f5ce9u,0x3d9064b4u},
  {0xbf7f4e6du,0x3d96a905u}, {0xbf7f3f54u,0x3d9cecf9u}, {0xbf7f2f9du,0x3da3308cu}, {0xbf7f1f49u,0x3da973bau}, {0xbf7f0e58u,0x3dafb680u}, {0xbf7efcc9u,0x3db5f8dau}, {0xbf7eea9du,0x3dbc3ac3u}, {0xbf7ed7d4u,0x3dc27c39u},
  {0xbf7ec46du,0x3dc8bd36u}, {0xbf7eb069u,0x3dcefdb7u}, {0xbf7e9bc9u,0x3dd53db9u}, {0xbf7e868bu,0x3ddb7d37u}, {0xbf7e70b0u,0x3de1bc2eu}, {0xbf7e5a38u,0x3de7fa9au}, {0xbf7e4323u,0x3dee3876u}, {0xbf7e2b72u,0x3df475c0u},
  {0xbf7e1324u,0x3dfab273u}, {0xbf7dfa38u,0x3e007745u}, {0xbf7de0b1u,0x3e039502u}, {0xbf7dc68cu,0x3e06b26eu}, {0xbf7dabccu,0x3e09cf86u}, {0xbf7d906eu,0x3e0cec4au}, {0xbf7d7474u,0x3e1008b7u}, {0xbf7d57deu,0x3e1324cau},
  {0xbf7d3aacu,0x3e164083u}, {0xbf7d1cddu,0x3e195be0u}, {0xbf7cfe73u,0x3e1c76deu}, {0xbf7cdf6cu,0x3e1f917bu}, {0xbf7cbfc9u,0x3e22abb6u}, {0xbf7c9f8au,0x3e25c58cu}, {0xbf7c7eb0u,0x3e28defcu}, {0xbf7c5d3au,0x3e2bf804u},
  {0xbf7c3b28u,0x3e2f10a2u}, {0xbf7c187au,0x3e3228d4u}, {0xbf7bf531u,0x3e354098u}, {0xbf7bd14du,0x3e3857ecu}, {0xbf7baccdu,0x3e3b6ecfu}, {0xbf7b87b2u,0x3e3e853eu}, {0xbf7b61fcu,0x3e419b37u}, {0xbf7b3babu,0x3e44b0b9u},
  {0xbf7b14beu,0x3e47c5c2u}, {0xbf7aed37u,0x3e4ada4fu}, {0xbf7ac516u,0x3e4dee60u}, {0xbf7a9c59u,0x3e5101f1u}, {0xbf7a7302u,0x3e541501u}, {0xbf7a4910u,0x3e57278fu}, {0xbf7a1e84u,0x3e5a3997u}, {0xbf79f35eu,0x3e5d4b1au},
  {0xbf79c79du,0x3e605c13u}, {0xbf799b43u,0x3e636c83u}, {0xbf796e4eu,0x3e667c66u}, {0xbf7940c0u,0x3e698bbau}, {0xbf791298u,0x3e6c9a7fu}, {0xbf78e3d6u,0x3e6fa8b2u}, {0xbf78b47bu,0x3e72b651u}, {0xbf788486u,0x3e75c35au},
  {0xbf7853f8u,0x3e78cfccu}, {0xbf7822d1u,0x3e7bdba4u}, {0xbf77f110u,0x3e7ee6e1u}, {0xbf77beb7u,0x3e80f8c0u}, {0xbf778bc5u,0x3e827dc0u}, {0xbf77583au,0x3e840270u}, {0xbf772417u,0x3e8586ceu}, {0xbf76ef5bu,0x3e870adau},
  {0xbf76ba07u,0x3e888e93u}, {0xbf76841bu,0x3e8a11f7u}, {0xbf764d97u,0x3e8b9507u}, {0xbf76167au,0x3e8d17c0u}, {0xbf75dec6u,0x3e8e9a22u}, {0xbf75a67bu,0x3e901c2cu}, {0xbf756d97u,0x3e919dddu}, {0xbf75341du,0x3e931f35u},
  {0xbf74fa0bu,0x3e94a031u}, {0xbf74bf62u,0x3e9620d2u}, {0xbf748422u,0x3e97a117u}, {0xbf74484bu,0x3e9920feu}, {0xbf740bddu,0x3e9aa086u}, {0xbf73ced9u,0x3e9c1fafu}, {0xbf73913fu,0x3e9d9e78u}, {0xbf73530eu,0x3e9f1cdfu},
  {0xbf731447u,0x3ea09ae5u}, {0xbf72d4ebu,0x3ea21887u}, {0xbf7294f8u,0x3ea395c5u}, {0xbf725470u,0x3ea5129fu}, {0xbf721352u,0x3ea68f12u}, {0xbf71d19fu,0x3ea80b1fu}, {0xbf718f57u,0x3ea986c4u}, {0xbf714c7au,0x3eab0201u},
  {0xbf710908u,0x3eac7cd4u}, {0xbf70c501u,0x3eadf73cu}, {0xbf708066u,0x3eaf713au}, {0xbf703b37u,0x3eb0eacbu}, {0xbf6ff573u,0x3eb263efu}, {0xbf6faf1bu,0x3eb3dca5u}, {0xbf6f6830u,0x3eb554ecu}, {0xbf6f20b0u,0x3eb6ccc3u},
  {0xbf6ed89eu,0x3eb8442au}, {0xbf6e8ff8u,0x3eb9bb1eu}, {0xbf6e46beu,0x3ebb31a0u}, {0xbf6dfcf2u,0x3ebca7afu}, {0xbf6db293u,0x3ebe1d4au}, {0xbf6d67a1u,0x3ebf926fu}, {0xbf6d1c1du,0x3ec1071eu}, {0xbf6cd007u,0x3ec27b55u},
  {0xbf6c835eu,0x3ec3ef15u}, {0xbf6c3624u,0x3ec5625cu}, {0xbf6be858u,0x3ec6d529u}, {0xbf6b99fbu,0x3ec8477cu}, {0xbf6b4b0cu,0x3ec9b953u}, {0xbf6afb8cu,0x3ecb2aaeu}, {0xbf6aab7bu,0x3ecc9b8bu}, {0xbf6a5ad9u,0x3ece0beau},
  {0xbf6a09a7u,0x3ecf7bcau}, {0xbf69b7e4u,0x3ed0eb2au}, {0xbf696591u,0x3ed25a09u}, {0xbf6912aeu,0x3ed3c867u}, {0xbf68bf3cu,0x3ed53641u}, {0xbf686b39u,0x3ed6a399u}, {0xbf6816a8u,0x3ed8106bu}, {0xbf67c187u,0x3ed97cb9u},
  {0xbf676bd8u,0x3edae880u}, {0xbf671599u,0x3edc53c1u}, {0xbf66beccu,0x3eddbe79u}, {0xbf666771u,0x3edf28a9u}, {0xbf660f88u,0x3ee0924fu}, {0xbf65b710u,0x3ee1fb6au}, {0xbf655e0bu,0x3ee363fau}, {0xbf650479u,0x3ee4cbfeu},
  {0xbf64aa59u,0x3ee63375u}, {0xbf644facu,0x3ee79a5du}, {0xbf63f473u,0x3ee900b7u}, {0xbf6398acu,0x3eea6681u}, {0xbf633c5au,0x3eebcbbbu}, {0xbf62df7bu,0x3eed3063u}, {0xbf628210u,0x3eee9479u}, {0xbf62241au,0x3eeff7fbu},
  {0xbf61c598u,0x3ef15aeau}, {0xbf61668au,0x3ef2bd43u}, {0xbf6106f2u,0x3ef41f07u}, {0xbf60a6cfu,0x3ef58035u}, {0xbf604621u,0x3ef6e0cbu}, {0xbf5fe4e9u,0x3ef840c8u}, {0xbf5f8327u,0x3ef9a02du}, {0xbf5f20dbu,0x3efafef7u},
  {0xbf5ebe05u,0x3efc5d27u}, {0xbf5e5aa6u,0x3efdbabbu}, {0xbf5df6beu,0x3eff17b2u}, {0xbf5d924du,0x3f003a06u}, {0xbf5d2d53u,0x3f00e7e4u}, {0xbf5cc7d1u,0x3f019573u}, {0xbf5c61c7u,0x3f0242b1u}, {0xbf5bfb34u,0x3f02ef9fu},
  {0xbf5b941au,0x3f039c3du}, {0xbf5b2c79u,0x3f044889u}, {0xbf5ac450u,0x3f04f484u}, {0xbf5a5ba0u,0x3f05a02cu}, {0xbf59f26au,0x3f064b82u}, {0xbf5988adu,0x3f06f686u}, {0xbf591e6au,0x3f07a136u}, {0xbf58b3a1u,0x3f084b92u},
  {0xbf584853u,0x3f08f59bu}, {0xbf57dc7fu,0x3f099f4eu}, {0xbf577026u,0x3f0a48adu}, {0xbf570348u,0x3f0af1b7u}, {0xbf5695e5u,0x3f0b9a6bu}, {0xbf5627feu,0x3f0c42c9u}, {0xbf55b993u,0x3f0cead0u}, {0xbf554aa4u,0x3f0d9281u},
  {0xbf54db31u,0x3f0e39dau}, {0xbf546b3bu,0x3f0ee0dbu}, {0xbf53fac3u,0x3f0f8784u}, {0xbf5389c7u,0x3f102dd5u}, {0xbf531849u,0x3f10d3cdu}, {0xbf52a649u,0x3f11796bu}, {0xbf5233c6u,0x3f121eb0u}, {0xbf51c0c2u,0x3f12c39au},
  {0xbf514d3du,0x3f13682au}, {0xbf50d937u,0x3f140c5fu}, {0xbf5064afu,0x3f14b039u}, {0xbf4fefa8u,0x3f1553b7u}, {0xbf4f7a1fu,0x3f15f6d9u}, {0xbf4f0417u,0x3f16999fu}, {0xbf4e8d90u,0x3f173c07u}, {0xbf4e1689u,0x3f17de12u},
  {0xbf4d9f02u,0x3f187fc0u}, {0xbf4d26fdu,0x3f19210fu}, {0xbf4cae79u,0x3f19c200u}, {0xbf4c3578u,0x3f1a6293u}, {0xbf4bbbf8u,0x3f1b02c6u}, {0xbf4b41fau,0x3f1ba299u}, {0xbf4ac77fu,0x3f1c420cu}, {0xbf4a4c87u,0x3f1ce11fu},
  {0xbf49d112u,0x3f1d7fd1u}, {0xbf495521u,0x3f1e1e22u}, {0xbf48d8b3u,0x3f1ebc12u}, {0xbf485bcau,0x3f1f599fu}, {0xbf47de65u,0x3f1ff6cbu}, {0xbf476085u,0x3f209393u}, {0xbf46e22au,0x3f212ff9u}, {0xbf466354u,0x3f21cbfbu},
  {0xbf45e403u,0x3f226799u}, {0xbf456439u,0x3f2302d3u}, {0xbf44e3f5u,0x3f239da9u}, {0xbf446337u,0x3f24381au}, {0xbf43e200u,0x3f24d225u}, {0xbf436051u,0x3f256bcbu}, {0xbf42de29u,0x3f26050au}, {0xbf425b89u,0x3f269de3u},
  {0xbf41d870u,0x3f273656u}, {0xbf4154e1u,0x3f27ce61u}, {0xbf40d0dau,0x3f286605u}, {0xbf404c5cu,0x3f28fd41u}, {0xbf3fc767u,0x3f299415u}, {0xbf3f41fcu,0x3f2a2a80u}, {0xbf3ebc1bu,0x3f2ac082u}, {0xbf3e35c5u,0x3f2b561bu},
  {0xbf3daef9u,0x3f2beb4au}, {0xbf3d27b8u,0x3f2c800fu}, {0xbf3ca003u,0x3f2d1469u}, {0xbf3c17d9u,0x3f2da859u}, {0xbf3b8f3bu,0x3f2e3bdeu}, {0xbf3b0629u,0x3f2ecef7u}, {0xbf3a7ca4u,0x3f2f61a5u}, {0xbf39f2acu,0x3f2ff3e6u},
  {0xbf396842u,0x3f3085bbu}, {0xbf38dd65u,0x3f311722u}, {0xbf385216u,0x3f31a81du}, {0xbf37c655u,0x3f3238aau}, {0xbf373a23u,0x3f32c8c9u}, {0xbf36ad7fu,0x3f33587au}, {0xbf36206cu,0x3f33e7bcu}, {0xbf3592e7u,0x3f34768fu},
  {0xbf3504f3u,0x3f3504f3u}, {0xbf34768fu,0x3f3592e7u}, {0xbf33e7bcu,0x3f36206cu}, {0xbf33587au,0x3f36ad7fu}, {0xbf32c8c9u,0x3f373a23u}, {0xbf3238aau,0x3f37c655u}, {0xbf31a81du,0x3f385216u}, {0xbf311722u,0x3f38dd65u},
  {0xbf3085bbu,0x3f396842u}, {0xbf2ff3e6u,0x3f39f2acu}, {0xbf2f61a5u,0x3f3a7ca4u}, {0xbf2ecef7u,0x3f3b0629u}, {0xbf2e3bdeu,0x3f3b8f3bu}, {0xbf2da859u,0x3f3c17d9u}, {0xbf2d1469u,0x3f3ca003u}, {0xbf2c800fu,0x3f3d27b8u},
  {0xbf2beb4au,0x3f3daef9u}, {0xbf2b561bu,0x3f3e35c5u}, {0xbf2ac082u,0x3f3ebc1bu}, {0xbf2a2a80u,0x3f3f41fcu}, {0xbf299415u,0x3f3fc767u}, {0xbf28fd41u,0x3f404c5cu}, {0xbf286605u,0x3f40d0dau}, {0xbf27ce61u,0x3f4154e1u},
  {0xbf273656u,0x3f41d870u}, {0xbf269de3u,0x3f425b89u}, {0xbf26050au,0x3f42de29u}, {0xbf256bcbu,0x3f436051u}, {0xbf24d225u,0x3f43e200u}, {0xbf24381au,0x3f446337u}, {0xbf239da9u,0x3f44e3f5u}, {0xbf2302d3u,0x3f456439u},
  {0xbf226799u,0x3f45e403u}, {0xbf21cbfbu,0x3f466354u}, {0xbf212ff9u,0x3f46e22au}, {0xbf209393u,0x3f476085u}, {0xbf1ff6cbu,0x3f47de65u}, {0xbf1f599fu,0x3f485bcau}, {0xbf1ebc12u,0x3f48d8b3u}, {0xbf1e1e22u,0x3f495521u},
  {0xbf1d7fd1u,0x3f49d112u}, {0xbf1ce11fu,0x3f4a4c87u}, {0xbf1c420cu,0x3f4ac77fu}, {0xbf1ba299u,0x3f4b41fau}, {0xbf1b02c6u,0x3f4bbbf8u}, {0xbf1a6293u,0x3f4c3578u}, {0xbf19c200u,0x3f4cae79u}, {0xbf19210fu,0x3f4d26fdu},
  {0xbf187fc0u,0x3f4d9f02u}, {0xbf17de12u,0x3f4e1689u}, {0xbf173c07u,0x3f4e8d90u}, {0xbf16999fu,0x3f4f0417u}, {0xbf15f6d9u,0x3f4f7a1fu}, {0xbf1553b7u,0x3f4fefa8u}, {0xbf14b039u,0x3f5064afu}, {0xbf140c5fu,0x3f50d937u},
  {0xbf13682au,0x3f514d3du}, {0xbf12c39au,0x3f51c0c2u}, {0xbf121eb0u,0x3f5233c6u}, {0xbf11796bu,0x3f52a649u}, {0xbf10d3cdu,0x3f531849u}, {0xbf102dd5u,0x3f5389c7u}, {0xbf0f8784u,0x3f53fac3u}, {0xbf0ee0dbu,0x3f546b3bu},
  {0xbf0e39dau,0x3f54db31u}, {0xbf0d9281u,0x3f554aa4u}, {0xbf0cead0u,0x3f55b993u}, {0xbf0c42c9u,0x3f5627feu}, {0xbf0b9a6bu,0x3f5695e5u}, {0xbf0af1b7u,0x3f570348u}, {0xbf0a48adu,0x3f577026u}, {0xbf099f4eu,0x3f57dc7fu},
  {0xbf08f59bu,0x3f584853u}, {0xbf084b92u,0x3f58b3a1u}, {0xbf07a136u,0x3f591e6au}, {0xbf06f686u,0x3f5988adu}, {0xbf064b82u,0x3f59f26au}, {0xbf05a02cu,0x3f5a5ba0u}, {0xbf04f484u,0x3f5ac450u}, {0xbf044889u,0x3f5b2c79u},
  {0xbf039c3du,0x3f5b941au}, {0xbf02ef9fu,0x3f5bfb34u}, {0xbf0242b1u,0x3f5c61c7u}, {0xbf019573u,0x3f5cc7d1u}, {0xbf00e7e4u,0x3f5d2d53u}, {0xbf003a06u,0x3f5d924du}, {0xbeff17b2u,0x3f5df6beu}, {0xbefdbabbu,0x3f5e5aa6u},
  {0xbefc5d27u,0x3f5ebe05u}, {0xbefafef7u,0x3f5f20dbu}, {0xbef9a02du,0x3f5f8327u}, {0xbef840c8u,0x3f5fe4e9u}, {0xbef6e0cbu,0x3f604621u}, {0xbef58035u,0x3f60a6cfu}, {0xbef41f07u,0x3f6106f2u}, {0xbef2bd43u,0x3f61668au},
  {0xbef15aeau,0x3f61c598u}, {0xbeeff7fbu,0x3f62241au}, {0xbeee9479u,0x3f628210u}, {0xbeed3063u,0x3f62df7bu}, {0xbeebcbbbu,0x3f633c5au}, {0xbeea6681u,0x3f6398acu}, {0xbee900b7u,0x3f63f473u}, {0xbee79a5du,0x3f644facu},
  {0xbee63375u,0x3f64aa59u}, {0xbee4cbfeu,0x3f650479u}, {0xbee363fau,0x3f655e0bu}, {0xbee1fb6au,0x3f65b710u}, {0xbee0924fu,0x3f660f88u}, {0xbedf28a9u,0x3f666771u}, {0xbeddbe79u,0x3f66beccu}, {0xbedc53c1u,0x3f671599u},
  {0xbedae880u,0x3f676bd8u}, {0xbed97cb9u,0x3f67c187u}, {0xbed8106bu,0x3f6816a8u}, {0xbed6a399u,0x3f686b39u}, {0xbed53641u,0x3f68bf3cu}, {0xbed3c867u,0x3f6912aeu}, {0xbed25a09u,0x3f696591u}, {0xbed0eb2au,0x3f69b7e4u},
  {0xbecf7bcau,0x3f6a09a7u}, {0xbece0beau,0x3f6a5ad9u}, {0xbecc9b8bu,0x3f6aab7bu}, {0xbecb2aaeu,0x3f6afb8cu}, {0xbec9b953u,0x3f6b4b0cu}, {0xbec8477cu,0x3f6b99fbu}, {0xbec6d529u,0x3f6be858u}, {0xbec5625cu,0x3f6c3624u},
  {0xbec3ef15u,0x3f6c835eu}, {0xbec27b55u,0x3f6cd007u}, {0xbec1071eu,0x3f6d1c1du}, {0xbebf926fu,0x3f6d67a1u}, {0xbebe1d4au,0x3f6db293u}, {0xbebca7afu,0x3f6dfcf2u}, {0xbebb31a0u,0x3f6e46beu}, {0xbeb9bb1eu,0x3f6e8ff8u},
  {0xbeb8442au,0x3f6ed89eu}, {0xbeb6ccc3u,0x3f6f20b0u}, {0xbeb554ecu,0x3f6f6830u}, {0xbeb3dca5u,0x3f6faf1bu}, {0xbeb263efu,0x3f6ff573u}, {0xbeb0eacbu,0x3f703b37u}, {0xbeaf713au,0x3f708066u}, {0xbeadf73cu,0x3f70c501u},
  {0xbeac7cd4u,0x3f710908u}, {0xbeab0201u,0x3f714c7au}, {0xbea986c4u,0x3f718f57u}, {0xbea80b1fu,0x3f71d19fu}, {0xbea68f12u,0x3f721352u}, {0xbea5129fu,0x3f725470u}, {0xbea395c5u,0x3f7294f8u}, {0xbea21887u,0x3f72d4ebu},
  {0xbea09ae5u,0x3f731447u}, {0xbe9f1cdfu,0x3f73530eu}, {0xbe9d9e78u,0x3f73913fu}, {0xbe9c1fafu,0x3f73ced9u}, {0xbe9aa086u,0x3f740bddu}, {0xbe9920feu,0x3f74484bu}, {0xbe97a117u,0x3f748422u}, {0xbe9620d2u,0x3f74bf62u},
  {0xbe94a031u,0x3f74fa0bu}, {0xbe931f35u,0x3f75341du}, {0xbe919dddu,0x3f756d97u}, {0xbe901c2cu,0x3f75a67bu}, {0xbe8e9a22u,0x3f75dec6u}, {0xbe8d17c0u,0x3f76167au}, {0xbe8b9507u,0x3f764d97u}, {0xbe8a11f7u,0x3f76841bu},
  {0xbe888e93u,0x3f76ba07u}, {0xbe870adau,0x3f76ef5bu}, {0xbe8586ceu,0x3f772417u}, {0xbe840270u,0x3f77583au}, {0xbe827dc0u,0x3f778bc5u}, {0xbe80f8c0u,0x3f77beb7u}, {0xbe7ee6e1u,0x3f77f110u}, {0xbe7bdba4u,0x3f7822d1u},
  {0xbe78cfccu,0x3f7853f8u}, {0xbe75c35au,0x3f788486u}, {0xbe72b651u,0x3f78b47bu}, {0xbe6fa8b2u,0x3f78e3d6u}, {0xbe6c9a7fu,0x3f791298u}, {0xbe698bbau,0x3f7940c0u}, {0xbe667c66u,0x3f796e4eu}, {0xbe636c83u,0x3f799b43u},
  {0xbe605c13u,0x3f79c79du}, {0xbe5d4b1au,0x3f79f35eu}, {0xbe5a3997u,0x3f7a1e84u}, {0xbe57278fu,0x3f7a4910u}, {0xbe541501u,0x3f7a7302u}, {0xbe5101f1u,0x3f7a9c59u}, {0xbe4dee60u,0x3f7ac516u}, {0xbe4ada4fu,0x3f7aed37u},
  {0xbe47c5c2u,0x3f7b14beu}, {0xbe44b0b9u,0x3f7b3babu}, {0xbe419b37u,0x3f7b61fcu}, {0xbe3e853eu,0x3f7b87b2u}, {0xbe3b6ecfu,0x3f7baccdu}, {0xbe3857ecu,0x3f7bd14du}, {0xbe354098u,0x3f7bf531u}, {0xbe3228d4u,0x3f7c187au},
  {0xbe2f10a2u,0x3f7c3b28u}, {0xbe2bf804u,0x3f7c5d3au}, {0xbe28defcu,0x3f7c7eb0u}, {0xbe25c58cu,0x3f7c9f8au}, {0xbe22abb6u,0x3f7cbfc9u}, {0xbe1f917bu,0x3f7cdf6cu}, {0xbe1c76deu,0x3f7cfe73u}, {0xbe195be0u,0x3f7d1cddu},
  {0xbe164083u,0x3f7d3aacu}, {0xbe1324cau,0x3f7d57deu}, {0xbe1008b7u,0x3f7d7474u}, {0xbe0cec4au,0x3f7d906eu}, {0xbe09cf86u,0x3f7dabccu}, {0xbe06b26eu,0x3f7dc68cu}, {0xbe039502u,0x3f7de0b1u}, {0xbe007745u,0x3f7dfa38u},
  {0xbdfab273u,0x3f7e1324u}, {0xbdf475c0u,0x3f7e2b72u}, {0xbdee3876u,0x3f7e4323u}, {0xbde7fa9au,0x3f7e5a38u}, {0xbde1bc2eu,0x3f7e70b0u}, {0xbddb7d37u,0x3f7e868bu}, {0xbdd53db9u,0x3f7e9bc9u}, {0xbdcefdb7u,0x3f7eb069u},
  {0xbdc8bd36u,0x3f7ec46du}, {0xbdc27c39u,0x3f7ed7d4u}, {0xbdbc3ac3u,0x3f7eea9du}, {0xbdb5f8dau,0x3f7efcc9u}, {0xbdafb680u,0x3f7f0e58u}, {0xbda973bau,0x3f7f1f49u}, {0xbda3308cu,0x3f7f2f9du}, {0xbd9cecf9u,0x3f7f3f54u},
  {0xbd96a905u,0x3f7f4e6du}, {0xbd9064b4u,0x3f7f5ce9u}, {0xbd8a200au,0x3f7f6ac7u}, {0xbd83db0au,0x3f7f7808u}, {0xbd7b2b74u,0x3f7f84abu}, {0xbd6ea038u,0x3f7f90b1u}, {0xbd621469u,0x3f7f9c18u}, {0xbd55880eu,0x3f7fa6e3u},
  {0xbd48fb30u,0x3f7fb10fu}, {0xbd3c6dd5u,0x3f7fba9eu}, {0xbd2fe007u,0x3f7fc38fu}, {0xbd2351cbu,0x3f7fcbe2u}, {0xbd16c32cu,0x3f7fd397u}, {0xbd0a342fu,0x3f7fdaafu}, {0xbcfb49bau,0x3f7fe129u}, {0xbce22a7au,0x3f7fe705u},
  {0xbcc90ab0u,0x3f7fec43u}, {0xbcafea69u,0x3f7ff0e3u}, {0xbc96c9b6u,0x3f7ff4e6u}, {0xbc7b514bu,0x3f7ff84au}, {0xbc490e90u,0x3f7ffb11u}, {0xbc16cb58u,0x3f7ffd39u}, {0xbbc90f88u,0x3f7ffec4u}, {0xbb490fc6u,0x3f7fffb1u},
  {0x00000000u,0x3f800000u}, {0x3b490fc6u,0x3f7fffb1u}, {0x3bc90f88u,0x3f7ffec4u}, {0x3c16cb58u,0x3f7ffd39u}, {0x3c490e90u,0x3f7ffb11u}, {0x3c7b514bu,0x3f7ff84au}, {0x3c96c9b6u,0x3f7ff4e6u}, {0x3cafea69u,0x3f7ff0e3u},
  {0x3cc90ab0u,0x3f7fec43u}, {0x3ce22a7au,0x3f7fe705u}, {0x3cfb49bau,0x3f7fe129u}, {0x3d0a342fu,0x3f7fdaafu}, {0x3d16c32cu,0x3f7fd397u}, {0x3d2351cbu,0x3f7fcbe2u}, {0x3d2fe007u,0x3f7fc38fu}, {0x3d3c6dd5u,0x3f7fba9eu},
  {0x3d48fb30u,0x3f7fb10fu}, {0x3d55880eu,0x3f7fa6e3u}, {0x3d621469u,0x3f7f9c18u}, {0x3d6ea038u,0x3f7f90b1u}, {0x3d7b2b74u,0x3f7f84abu}, {0x3d83db0au,0x3f7f7808u}, {0x3d8a200au,0x3f7f6ac7u}, {0x3d9064b4u,0x3f7f5ce9u},
  {0x3d96a905u,0x3f7f4e6du}, {0x3d9cecf9u,0x3f7f3f54u}, {0x3da3308cu,0x3f7f2f9du}, {0x3da973bau,0x3f7f1f49u}, {0x3dafb680u,0x3f7f0e58u}, {0x3db5f8dau,0x3f7efcc9u}, {0x3dbc3ac3u,0x3f7eea9du}, {0x3dc27c39u,0x3f7ed7d4u},
  {0x3dc8bd36u,0x3f7ec46du}, {0x3dcefdb7u,0x3f7eb069u}, {0x3dd53db9u,0x3f7e9bc9u}, {0x3ddb7d37u,0x3f7e868bu}, {0x3de1bc2eu,0x3f7e70b0u}, {0x3de7fa9au,0x3f7e5a38u}, {0x3dee3876u,0x3f7e4323u}, {0x3df475c0u,0x3f7e2b72u},
  {0x3dfab273u,0x3f7e1324u}, {0x3e007745u,0x3f7dfa38u}, {0x3e039502u,0x3f7de0b1u}, {0x3e06b26eu,0x3f7dc68cu}, {0x3e09cf86u,0x3f7dabccu}, {0x3e0cec4au,0x3f7d906eu}, {0x3e1008b7u,0x3f7d7474u}, {0x3e1324cau,0x3f7d57deu},
  {0x3e164083u,0x3f7d3aacu}, {0x3e195be0u,0x3f7d1cddu}, {0x3e1c76deu,0x3f7cfe73u}, {0x3e1f917bu,0x3f7cdf6cu}, {0x3e22abb6u,0x3f7cbfc9u}, {0x3e25c58cu,0x3f7c9f8au}, {0x3e28defcu,0x3f7c7eb0u}, {0x3e2bf804u,0x3f7c5d3au},
  {0x3e2f10a2u,0x3f7c3b28u}, {0x3e3228d4u,0x3f7c187au}, {0x3e354098u,0x3f7bf531u}, {0x3e3857ecu,0x3f7bd14du}, {0x3e3b6ecfu,0x3f7baccdu}, {0x3e3e853eu,0x3f7b87b2u}, {0x3e419b37u,0x3f7b61fcu}, {0x3e44b0b9u,0x3f7b3babu},
  {0x3e47c5c2u,0x3f7b14beu}, {0x3e4ada4fu,0x3f7aed37u}, {0x3e4dee60u,0x3f7ac516u}, {0x3e5101f1u,0x3f7a9c59u}, {0x3e541501u,0x3f7a7302u}, {0x3e57278fu,0x3f7a4910u}, {0x3e5a3997u,0x3f7a1e84u}, {0x3e5d4b1au,0x3f79f35eu},
  {0x3e605c13u,0x3f79c79du}, {0x3e636c83u,0x3f799b43u}, {0x3e667c66u,0x3f796e4eu}, {0x3e698bbau,0x3f7940c0u}, {0x3e6c9a7fu,0x3f791298u}, {0x3e6fa8b2u,0x3f78e3d6u}, {0x3e72b651u,0x3f78b47bu}, {0x3e75c35au,0x3f788486u},
  {0x3e78cfccu,0x3f7853f8u}, {0x3e7bdba4u,0x3f7822d1u}, {0x3e7ee6e1u,0x3f77f110u}, {0x3e80f8c0u,0x3f77beb7u}, {0x3e827dc0u,0x3f778bc5u}, {0x3e840270u,0x3f77583au}, {0x3e8586ceu,0x3f772417u}, {0x3e870adau,0x3f76ef5bu},
  {0x3e888e93u,0x3f76ba07u}, {0x3e8a11f7u,0x3f76841bu}, {0x3e8b9507u,0x3f764d97u}, {0x3e8d17c0u,0x3f76167au}, {0x3e8e9a22u,0x3f75dec6u}, {0x3e901c2cu,0x3f75a67bu}, {0x3e919dddu,0x3f756d97u}, {0x3e931f35u,0x3f75341du},
  {0x3e94a031u,0x3f74fa0bu}, {0x3e9620d2u,0x3f74bf62u}, {0x3e97a117u,0x3f748422u}, {0x3e9920feu,0x3f74484bu}, {0x3e9aa086u,0x3f740bddu}, {0x3e9c1fafu,0x3f73ced9u}, {0x3e9d9e78u,0x3f73913fu}, {0x3e9f1cdfu,0x3f73530eu},
  {0x3ea09ae5u,0x3f731447u}, {0x3ea21887u,0x3f72d4ebu}, {0x3ea395c5u,0x3f7294f8u}, {0x3ea5129fu,0x3f725470u}, {0x3ea68f12u,0x3f721352u}, {0x3ea80b1fu,0x3f71d19fu}, {0x3ea986c4u,0x3f718f57u}, {0x3eab0201u,0x3f714c7au},
  {0x3eac7cd4u,0x3f710908u}, {0x3eadf73cu,0x3f70c501u}, {0x3eaf713au,0x3f708066u}, {0x3eb0eacbu,0x3f703b37u}, {0x3eb263efu,0x3f6ff573u}, {0x3eb3dca5u,0x3f6faf1bu}, {0x3eb554ecu,0x3f6f6830u}, {0x3eb6ccc3u,0x3f6f20b0u},
  {0x3eb8442au,0x3f6ed89eu}, {0x3eb9bb1eu,0x3f6e8ff8u}, {0x3ebb31a0u,0x3f6e46beu}, {0x3ebca7afu,0x3f6dfcf2u}, {0x3ebe1d4au,0x3f6db293u}, {0x3ebf926fu,0x3f6d67a1u}, {0x3ec1071eu,0x3f6d1c1du}, {0x3ec27b55u,0x3f6cd007u},
  {0x3ec3ef15u,0x3f6c835eu}, {0x3ec5625cu,0x3f6c3624u}, {0x3ec6d529u,0x3f6be858u}, {0x3ec8477cu,0x3f6b99fbu}, {0x3ec9b953u,0x3f6b4b0cu}, {0x3ecb2aaeu,0x3f6afb8cu}, {0x3ecc9b8bu,0x3f6aab7bu}, {0x3ece0beau,0x3f6a5ad9u},
  {0x3ecf7bcau,0x3f6a09a7u}, {0x3ed0eb2au,0x3f69b7e4u}, {0x3ed25a09u,0x3f696591u}, {0x3ed3c867u,0x3f6912aeu}, {0x3ed53641u,0x3f68bf3cu}, {0x3ed6a399u,0x3f686b39u}, {0x3ed8106bu,0x3f6816a8u}, {0x3ed97cb9u,0x3f67c187u},
  {0x3edae880u,0x3f676bd8u}, {0x3edc53c1u,0x3f671599u}, {0x3eddbe79u,0x3f66beccu}, {0x3edf28a9u,0x3f666771u}, {0x3ee0924fu,0x3f660f88u}, {0x3ee1fb6au,0x3f65b710u}, {0x3ee363fau,0x3f655e0bu}, {0x3ee4cbfeu,0x3f650479u},
  {0x3ee63375u,0x3f64aa59u}, {0x3ee79a5du,0x3f644facu}, {0x3ee900b7u,0x3f63f473u}, {0x3eea6681u,0x3f6398acu}, {0x3eebcbbbu,0x3f633c5au}, {0x3eed3063u,0x3f62df7bu}, {0x3eee9479u,0x3f628210u}, {0x3eeff7fbu,0x3f62241au},
  {0x3ef15aeau,0x3f61c598u}, {0x3ef2bd43u,0x3f61668au}, {0x3ef41f07u,0x3f6106f2u}, {0x3ef58035u,0x3f60a6cfu}, {0x3ef6e0cbu,0x3f604621u}, {0x3ef840c8u,0x3f5fe4e9u}, {0x3ef9a02du,0x3f5f8327u}, {0x3efafef7u,0x3f5f20dbu},
  {0x3efc5d27u,0x3f5ebe05u}, {0x3efdbabbu,0x3f5e5aa6u}, {0x3eff17b2u,0x3f5df6beu}, {0x3f003a06u,0x3f5d924du}, {0x3f00e7e4u,0x3f5d2d53u}, {0x3f019573u,0x3f5cc7d1u}, {0x3f0242b1u,0x3f5c61c7u}, {0x3f02ef9fu,0x3f5bfb34u},
  {0x3f039c3du,0x3f5b941au}, {0x3f044889u,0x3f5b2c79u}, {0x3f04f484u,0x3f5ac450u}, {0x3f05a02cu,0x3f5a5ba0u}, {0x3f064b82u,0x3f59f26au}, {0x3f06f686u,0x3f5988adu}, {0x3f07a136u,0x3f591e6au}, {0x3f084b92u,0x3f58b3a1u},
  {0x3f08f59bu,0x3f584853u}, {0x3f099f4eu,0x3f57dc7fu}, {0x3f0a48adu,0x3f577026u}, {0x3f0af1b7u,0x3f570348u}, {0x3f0b9a6bu,0x3f5695e5u}, {0x3f0c42c9u,0x3f5627feu}, {0x3f0cead0u,0x3f55b993u}, {0x3f0d9281u,0x3f554aa4u},
  {0x3f0e39dau,0x3f54db31u}, {0x3f0ee0dbu,0x3f546b3bu}, {0x3f0f8784u,0x3f53fac3u}, {0x3f102dd5u,0x3f5389c7u}, {0x3f10d3cdu,0x3f531849u}, {0x3f11796bu,0x3f52a649u}, {0x3f121eb0u,0x3f5233c6u}, {0x3f12c39au,0x3f51c0c2u},
  {0x3f13682au,0x3f514d3du}, {0x3f140c5fu,0x3f50d937u}, {0x3f14b039u,0x3f5064afu}, {0x3f1553b7u,0x3f4fefa8u}, {0x3f15f6d9u,0x3f4f7a1fu}, {0x3f16999fu,0x3f4f0417u}, {0x3f173c07u,0x3f4e8d90u}, {0x3f17de12u,0x3f4e1689u},
  {0x3f187fc0u,0x3f4d9f02u}, {0x3f19210fu,0x3f4d26fdu}, {0x3f19c200u,0x3f4cae79u}, {0x3f1a6293u,0x3f4c3578u}, {0x3f1b02c6u,0x3f4bbbf8u}, {0x3f1ba299u,0x3f4b41fau}, {0x3f1c420cu,0x3f4ac77fu}, {0x3f1ce11fu,0x3f4a4c87u},
  {0x3f1d7fd1u,0x3f49d112u}, {0x3f1e1e22u,0x3f495521u}, {0x3f1ebc12u,0x3f48d8b3u}, {0x3f1f599fu,0x3f485bcau}, {0x3f1ff6cbu,0x3f47de65u}, {0x3f209393u,0x3f476085u}, {0x3f212ff9u,0x3f46e22au}, {0x3f21cbfbu,0x3f466354u},
  {0x3f226799u,0x3f45e403u}, {0x3f2302d3u,0x3f456439u}, {0x3f239da9u,0x3f44e3f5u}, {0x3f24381au,0x3f446337u}, {0x3f24d225u,0x3f43e200u}, {0x3f256bcbu,0x3f436051u}, {0x3f26050au,0x3f42de29u}, {0x3f269de3u,0x3f425b89u},
  {0x3f273656u,0x3f41d870u}, {0x3f27ce61u,0x3f4154e1u}, {0x3f286605u,0x3f40d0dau}, {0x3f28fd41u,0x3f404c5cu}, {0x3f299415u,0x3f3fc767u}, {0x3f2a2a80u,0x3f3f41fcu}, {0x3f2ac082u,0x3f3ebc1bu}, {0x3f2b561bu,0x3f3e35c5u},
  {0x3f2beb4au,0x3f3daef9u}, {0x3f2c800fu,0x3f3d27b8u}, {0x3f2d1469u,0x3f3ca003u}, {0x3f2da859u,0x3f3c17d9u}, {0x3f2e3bdeu,0x3f3b8f3bu}, {0x3f2ecef7u,0x3f3b0629u}, {0x3f2f61a5u,0x3f3a7ca4u}, {0x3f2ff3e6u,0x3f39f2acu},
  {0x3f3085bbu,0x3f396842u}, {0x3f311722u,0x3f38dd65u}, {0x3f31a81du,0x3f385216u}, {0x3f3238aau,0x3f37c655u}, {0x3f32c8c9u,0x3f373a23u}, {0x3f33587au,0x3f36ad7fu}, {0x3f33e7bcu,0x3f36206cu}, {0x3f34768fu,0x3f3592e7u},
  {0x3f3504f3u,0x3f3504f3u}, {0x3f3592e7u,0x3f34768fu}, {0x3f36206cu,0x3f33e7bcu}, {0x3f36ad7fu,0x3f33587au}, {0x3f373a23u,0x3f32c8c9u}, {0x3f37c655u,0x3f3238aau}, {0x3f385216u,0x3f31a81du}, {0x3f38dd65u,0x3f311722u},
  {0x3f396842u,0x3f3085bbu}, {0x3f39f2acu,0x3f2ff3e6u}, {0x3f3a7ca4u,0x3f2f61a5u}, {0x3f3b0629u,0x3f2ecef7u}, {0x3f3b8f3bu,0x3f2e3bdeu}, {0x3f3c17d9u,0x3f2da859u}, {0x3f3ca003u,0x3f2d1469u}, {0x3f3d27b8u,0x3f2c800fu},
  {0x3f3daef9u,0x3f2beb4au}, {0x3f3e35c5u,0x3f2b561bu}, {0x3f3ebc1bu,0x3f2ac082u}, {0x3f3f41fcu,0x3f2a2a80u}, {0x3f3fc767u,0x3f299415u}, {0x3f404c5cu,0x3f28fd41u}, {0x3f40d0dau,0x3f286605u}, {0x3f4154e1u,0x3f27ce61u},
  {0x3f41d870u,0x3f273656u}, {0x3f425b89u,0x3f269de3u}, {0x3f42de29u,0x3f26050au}, {0x3f436051u,0x3f256bcbu}, {0x3f43e200u,0x3f24d225u}, {0x3f446337u,0x3f24381au}, {0x3f44e3f5u,0x3f239da9u}, {0x3f456439u,0x3f2302d3u},
  {0x3f45e403u,0x3f226799u}, {0x3f466354u,0x3f21cbfbu}, {0x3f46e22au,0x3f212ff9u}, {0x3f476085u,0x3f209393u}, {0x3f47de65u,0x3f1ff6cbu}, {0x3f485bcau,0x3f1f599fu}, {0x3f48d8b3u,0x3f1ebc12u}, {0x3f495521u,0x3f1e1e22u},
  {0x3f49d112u,0x3f1d7fd1u}, {0x3f4a4c87u,0x3f1ce11fu}, {0x3f4ac77fu,0x3f1c420cu}, {0x3f4b41fau,0x3f1ba299u}, {0x3f4bbbf8u,0x3f1b02c6u}, {0x3f4c3578u,0x3f1a6293u}, {0x3f4cae79u,0x3f19c200u}, {0x3f4d26fdu,0x3f19210fu},
  {0x3f4d9f02u,0x3f187fc0u}, {0x3f4e1689u,0x3f17de12u}, {0x3f4e8d90u,0x3f173c07u}, {0x3f4f0417u,0x3f16999fu}, {0x3f4f7a1fu,0x3f15f6d9u}, {0x3f4fefa8u,0x3f1553b7u}, {0x3f5064afu,0x3f14b039u}, {0x3f50d937u,0x3f140c5fu},
  {0x3f514d3du,0x3f13682au}, {0x3f51c0c2u,0x3f12c39au}, {0x3f5233c6u,0x3f121eb0u}, {0x3f52a649u,0x3f11796bu}, {0x3f531849u,0x3f10d3cdu}, {0x3f5389c7u,0x3f102dd5u}, {0x3f53fac3u,0x3f0f8784u}, {0x3f546b3bu,0x3f0ee0dbu},
  {0x3f54db31u,0x3f0e39dau}, {0x3f554aa4u,0x3f0d9281u}, {0x3f55b993u,0x3f0cead0u}, {0x3f5627feu,0x3f0c42c9u}, {0x3f5695e5u,0x3f0b9a6bu}, {0x3f570348u,0x3f0af1b7u}, {0x3f577026u,0x3f0a48adu}, {0x3f57dc7fu,0x3f099f4eu},
  {0x3f584853u,0x3f08f59bu}, {0x3f58b3a1u,0x3f084b92u}, {0x3f591e6au,0x3f07a136u}, {0x3f5988adu,0x3f06f686u}, {0x3f59f26au,0x3f064b82u}, {0x3f5a5ba0u,0x3f05a02cu}, {0x3f5ac450u,0x3f04f484u}, {0x3f5b2c79u,0x3f044889u},
  {0x3f5b941au,0x3f039c3du}, {0x3f5bfb34u,0x3f02ef9fu}, {0x3f5c61c7u,0x3f0242b1u}, {0x3f5cc7d1u,0x3f019573u}, {0x3f5d2d53u,0x3f00e7e4u}, {0x3f5d924du,0x3f003a06u}, {0x3f5df6beu,0x3eff17b2u}, {0x3f5e5aa6u,0x3efdbabbu},
  {0x3f5ebe05u,0x3efc5d27u}, {0x3f5f20dbu,0x3efafef7u}, {0x3f5f8327u,0x3ef9a02du}, {0x3f5fe4e9u,0x3ef840c8u}, {0x3f604621u,0x3ef6e0cbu}, {0x3f60a6cfu,0x3ef58035u}, {0x3f6106f2u,0x3ef41f07u}, {0x3f61668au,0x3ef2bd43u},
  {0x3f61c598u,0x3ef15aeau}, {0x3f62241au,0x3eeff7fbu}, {0x3f628210u,0x3eee9479u}, {0x3f62df7bu,0x3eed3063u}, {0x3f633c5au,0x3eebcbbbu}, {0x3f6398acu,0x3eea6681u}, {0x3f63f473u,0x3ee900b7u}, {0x3f644facu,0x3ee79a5du},
  {0x3f64aa59u,0x3ee63375u}, {0x3f650479u,0x3ee4cbfeu}, {0x3f655e0bu,0x3ee363fau}, {0x3f65b710u,0x3ee1fb6au}, {0x3f660f88u,0x3ee0924fu}, {0x3f666771u,0x3edf28a9u}, {0x3f66beccu,0x3eddbe79u}, {0x3f671599u,0x3edc53c1u},
  {0x3f676bd8u,0x3edae880u}, {0x3f67c187u,0x3ed97cb9u}, {0x3f6816a8u,0x3ed8106bu}, {0x3f686b39u,0x3ed6a399u}, {0x3f68bf3cu,0x3ed53641u}, {0x3f6912aeu,0x3ed3c867u}, {0x3f696591u,0x3ed25a09u}, {0x3f69b7e4u,0x3ed0eb2au},
  {0x3f6a09a7u,0x3ecf7bcau}, {0x3f6a5ad9u,0x3ece0beau}, {0x3f6aab7bu,0x3ecc9b8bu}, {0x3f6afb8cu,0x3ecb2aaeu}, {0x3f6b4b0cu,0x3ec9b953u}, {0x3f6b99fbu,0x3ec8477cu}, {0x3f6be858u,0x3ec6d529u}, {0x3f6c3624u,0x3ec5625cu},
  {0x3f6c835eu,0x3ec3ef15u}, {0x3f6cd007u,0x3ec27b55u}, {0x3f6d1c1du,0x3ec1071eu}, {0x3f6d67a1u,0x3ebf926fu}, {0x3f6db293u,0x3ebe1d4au}, {0x3f6dfcf2u,0x3ebca7afu}, {0x3f6e46beu,0x3ebb31a0u}, {0x3f6e8ff8u,0x3eb9bb1eu},
  {0x3f6ed89eu,0x3eb8442au}, {0x3f6f20b0u,0x3eb6ccc3u}, {0x3f6f6830u,0x3eb554ecu}, {0x3f6faf1bu,0x3eb3dca5u}, {0x3f6ff573u,0x3eb263efu}, {0x3f703b37u,0x3eb0eacbu}, {0x3f708066u,0x3eaf713au}, {0x3f70c501u,0x3eadf73cu},
  {0x3f710908u,0x3eac7cd4u}, {0x3f714c7au,0x3eab0201u}, {0x3f718f57u,0x3ea986c4u}, {0x3f71d19fu,0x3ea80b1fu}, {0x3f721352u,0x3ea68f12u}, {0x3f725470u,0x3ea5129fu}, {0x3f7294f8u,0x3ea395c5u}, {0x3f72d4ebu,0x3ea21887u},
  {0x3f731447u,0x3ea09ae5u}, {0x3f73530eu,0x3e9f1cdfu}, {0x3f73913fu,0x3e9d9e78u}, {0x3f73ced9u,0x3e9c1fafu}, {0x3f740bddu,0x3e9aa086u}, {0x3f74484bu,0x3e9920feu}, {0x3f748422u,0x3e97a117u}, {0x3f74bf62u,0x3e9620d2u},
  {0x3f74fa0bu,0x3e94a031u}, {0x3f75341du,0x3e931f35u}, {0x3f756d97u,0x3e919dddu}, {0x3f75a67bu,0x3e901c2cu}, {0x3f75dec6u,0x3e8e9a22u}, {0x3f76167au,0x3e8d17c0u}, {0x3f764d97u,0x3e8b9507u}, {0x3f76841bu,0x3e8a11f7u},
  {0x3f76ba07u,0x3e888e93u}, {0x3f76ef5bu,0x3e870adau}, {0x3f772417u,0x3e8586ceu}, {0x3f77583au,0x3e840270u}, {0x3f778bc5u,0x3e827dc0u}, {0x3f77beb7u,0x3e80f8c0u}, {0x3f77f110u,0x3e7ee6e1u}, {0x3f7822d1u,0x3e7bdba4u},
  {0x3f7853f8u,0x3e78cfccu}, {0x3f788486u,0x3e75c35au}, {0x3f78b47bu,0x3e72b651u}, {0x3f78e3d6u,0x3e6fa8b2u}, {0x3f791298u,0x3e6c9a7fu}, {0x3f7940c0u,0x3e698bbau}, {0x3f796e4eu,0x3e667c66u}, {0x3f799b43u,0x3e636c83u},
  {0x3f79c79du,0x3e605c13u}, {0x3f79f35eu,0x3e5d4b1au}, {0x3f7a1e84u,0x3e5a3997u}, {0x3f7a4910u,0x3e57278fu}, {0x3f7a7302u,0x3e541501u}, {0x3f7a9c59u,0x3e5101f1u}, {0x3f7ac516u,0x3e4dee60u}, {0x3f7aed37u,0x3e4ada4fu},
  {0x3f7b14beu,0x3e47c5c2u}, {0x3f7b3babu,0x3e44b0b9u}, {0x3f7b61fcu,0x3e419b37u}, {0x3f7b87b2u,0x3e3e853eu}, {0x3f7baccdu,0x3e3b6ecfu}, {0x3f7bd14du,0x3e3857ecu}, {0x3f7bf531u,0x3e354098u}, {0x3f7c187au,0x3e3228d4u},
  {0x3f7c3b28u,0x3e2f10a2u}, {0x3f7c5d3au,0x3e2bf804u}, {0x3f7c7eb0u,0x3e28defcu}, {0x3f7c9f8au,0x3e25c58cu}, {0x3f7cbfc9u,0x3e22abb6u}, {0x3f7cdf6cu,0x3e1f917bu}, {0x3f7cfe73u,0x3e1c76deu}, {0x3f7d1cddu,0x3e195be0u},
  {0x3f7d3aacu,0x3e164083u}, {0x3f7d57deu,0x3e1324cau}, {0x3f7d7474u,0x3e1008b7u}, {0x3f7d906eu,0x3e0cec4au}, {0x3f7dabccu,0x3e09cf86u}, {0x3f7dc68cu,0x3e06b26eu}, {0x3f7de0b1u,0x3e039502u}, {0x3f7dfa38u,0x3e007745u},
  {0x3f7e1324u,0x3dfab273u}, {0x3f7e2b72u,0x3df475c0u}, {0x3f7e4323u,0x3dee3876u}, {0x3f7e5a38u,0x3de7fa9au}, {0x3f7e70b0u,0x3de1bc2eu}, {0x3f7e868bu,0x3ddb7d37u}, {0x3f7e9bc9u,0x3dd53db9u}, {0x3f7eb069u,0x3dcefdb7u},
  {0x3f7ec46du,0x3dc8bd36u}, {0x3f7ed7d4u,0x3dc27c39u}, {0x3f7eea9du,0x3dbc3ac3u}, {0x3f7efcc9u,0x3db5f8dau}, {0x3f7f0e58u,0x3dafb680u}, {0x3f7f1f49u,0x3da973bau}, {0x3f7f2f9du,0x3da3308cu}, {0x3f7f3f54u,0x3d9cecf9u},
  {0x3f7f4e6du,0x3d96a905u}, {0x3f7f5ce9u,0x3d9064b4u}, {0x3f7f6ac7u,0x3d8a200au}, {0x3f7f7808u,0x3d83db0au}, {0x3f7f84abu,0x3d7b2b74u}, {0x3f7f90b1u,0x3d6ea038u}, {0x3f7f9c18u,0x3d621469u}, {0x3f7fa6e3u,0x3d55880eu},
  {0x3f7fb10fu,0x3d48fb30u}, {0x3f7fba9eu,0x3d3c6dd5u}, {0x3f7fc38fu,0x3d2fe007u}, {0x3f7fcbe2u,0x3d2351cbu}, {0x3f7fd397u,0x3d16c32cu}, {0x3f7fdaafu,0x3d0a342fu}, {0x3f7fe129u,0x3cfb49bau}, {0x3f7fe705u,0x3ce22a7au},
  {0x3f7fec43u,0x3cc90ab0u}, {0x3f7ff0e3u,0x3cafea69u}, {0x3f7ff4e6u,0x3c96c9b6u}, {0x3f7ff84au,0x3c7b514bu}, {0x3f7ffb11u,0x3c490e90u}, {0x3f7ffd39u,0x3c16cb58u}, {0x3f7ffec4u,0x3bc90f88u}, {0x3f7fffb1u,0x3b490fc6u},
};

__device__ __forceinline__ float2 twiddle(int num, int den) {
  float2 v;
  asm volatile("ld.global.nc.v2.f32 {%0,%1}, [%2];" : "=f"(v.x), "=f"(v.y) : "l"(c_w2048 + ((num * (2048 / den)) & 2047)));
  return v;
}
__device__ __forceinline__ uint4 lane_const(int q, int lane) {
  uint4 v;
  asm volatile("ld.global.nc.v4.b32 {%0,%1,%2,%3}, [%4];" : "=r"(v.x), "=r"(v.y), "=r"(v.z), "=r"(v.w) : "l"(c_lane + q * 32 + lane));
  return v;
}
__device__ __forceinline__ void lane_tw(float2 (&tw)[2][4], int q0, int lane) {
#pragma unroll
  for (int q = 0; q < 4; q++) {
    uint4 v = lane_const(q0 + q, lane);
    tw[q >> 1][(q & 1) * 2] = make_float2(__uint_as_float(v.x), __uint_as_float(v.y));
    tw[q >> 1][(q & 1) * 2 + 1] = make_float2(__uint_as_float(v.z), __uint_as_float(v.w));
  }
}

__device__ __forceinline__ void mma16816(float2& c0, float2& c1, uint32_t a0, uint32_t a1, uint32_t a2, uint32_t a3, uint32_t b0, uint32_t b1) {
  asm volatile("mma.sync.aligned.m16n8k16.row.col.f32.f16.f16.f32 {%0,%1,%2,%3}, {%4,%5,%6,%7}, {%8,%9}, {%0,%1,%2,%3};"
               : "+f"(c0.x), "+f"(c0.y), "+f"(c1.x), "+f"(c1.y) : "r"(a0), "r"(a1), "r"(a2), "r"(a3), "r"(b0), "r"(b1));
}
template <int N>
__device__ __forceinline__ void dft_frags(uint32_t (&bf)[2][4][2], int lane) {
#pragma unroll
  for (int q = 0; q < N / 4; q++) {
    uint4 v = lane_const((N == 16 ? 0 : 4) + q, lane);
    const int ks = N == 16 ? q >> 1 : q, j = N == 16 ? (q & 1) * 2 : q * 2;
    bf[ks][j][0] = v.x; bf[ks][j][1] = v.y; bf[ks][j + 1][0] = v.z; bf[ks][j + 1][1] = v.w;
  }
}
template <int N>
__device__ __forceinline__ void dft_tile(const uint32_t (&in)[2][4], float2 (&out)[2][4], const uint32_t (&bf)[2][4][2]) {
#pragma unroll
  for (int j = 0; j < 4; j++) {
    out[0][j] = make_float2(0.f, 0.f);
    out[1][j] = make_float2(0.f, 0.f);
#pragma unroll
    for (int ks = 0; ks < 2; ks++)
      if (N == 16 || (j >> 1) == ks)
        mma16816(out[0][j], out[1][j], in[0][2 * ks], in[1][2 * ks], in[0][2 * ks + 1], in[1][2 * ks + 1], bf[ks][j][0], bf[ks][j][1]);
  }
}
__device__ __forceinline__ void warp_transpose(const uint32_t (&v)[2][4], uint32_t (&o)[2][4], uint32_t buf  , int g, int t) {
  const uint32_t wb = buf + 4 * (((g & 1) << 4) | ((t >> 1) << 3) | ((g >> 1) << 1) | (t & 1) | ((g >> 1) << 6));
#pragma unroll
  for (int b = 0; b < 2; b++)
#pragma unroll
    for (int j = 0; j < 4; j++)
      asm volatile("st.shared.u32 [%0], %1;" ::"r"(wb ^ (4 * ((j << 1) | b) + 128 * b)), "r"(v[b][j]) : "memory");
  __syncwarp();
  const uint32_t rb = buf + 4 * (((t >> 1) << 4) | ((g & 1) << 3) | ((g >> 1) << 1) | (t & 1) | ((t & 1) << 5));
#pragma unroll
  for (int b = 0; b < 2; b++)
#pragma unroll
    for (int i = 0; i < 4; i++)
      asm volatile("ld.shared.u32 %0, [%1];" : "=r"(o[b][i]) : "r"(rb ^ (4 * ((i << 1) | b) + 256 * i)) : "memory");
}

__device__ __forceinline__ void row_stats(const float2 (&v)[2][4], float& mean, float& var) {
  const float piv = __shfl_sync(0xffffffffu, v[0][0].x, 0);
  float sp[4], qp[4];
#pragma unroll
  for (int i = 0; i < 4; i++) {
    float a = v[0][i].x - piv, c = v[0][i].y - piv, d = v[1][i].x - piv, e = v[1][i].y - piv;
    sp[i] = (a + c) + (d + e);
    qp[i] = fmaf(a, a, c * c) + fmaf(d, d, e * e);
  }
  float s = (sp[0] + sp[1]) + (sp[2] + sp[3]), q = (qp[0] + qp[1]) + (qp[2] + qp[3]);
#pragma unroll
  for (int o = 1; o < 32; o <<= 1) {
    s += __shfl_xor_sync(0xffffffffu, s, o);
    q += __shfl_xor_sync(0xffffffffu, q, o);
  }
  const float ms = s * (1.f / 512.f);
  mean = piv + ms;
  var = fmaxf(fmaf(-ms, ms, q * (1.f / 512.f)), 0.f);
}
__device__ __forceinline__ void ln_coef(float mean, float var, float& mb, float& r) {
  mb = bf16r(mean);
  float sq;
  asm("sqrt.approx.f32 %0, %1;" : "=f"(sq) : "f"(bf16r(bf16r(var) + 1e-5f)));
  asm("rcp.approx.f32 %0, %1;" : "=f"(r) : "f"(bf16r(sq)));
}
__device__ __forceinline__ float filter_scale(uint4 m4, bool inverse) {
  uint32_t m = max(max(m4.x, m4.y), max(m4.z, m4.w));
  m = __reduce_max_sync(0xffffffffu, m);
  int e = (int)(((m << 16) + 0x007fffffu) >> 23);
  int we = m == 0u ? 127 : min(max(254 - e, 1), 249);
  return __uint_as_float((uint32_t)(inverse ? 250 - we : we) << 23);
}

constexpr int RP = 324;
__device__ __forceinline__ int kpad(int k) { return k + 4 * (k >> 4); }
constexpr int R_SMEM = 16 * RP * 8 + 16 * 256 * 4;

__global__ void __launch_bounds__(640, 1) k_row_fwd(const __nv_bfloat16* __restrict__ x, int x_is_input,
                                                    const __nv_bfloat16* __restrict__ wr, const __nv_bfloat16* __restrict__ wi,
                                                    const void* pf0, int pf0_bytes) {
  extern __shared__ __align__(1024) uint32_t rsm[];
  float2* zs = reinterpret_cast<float2*>(rsm + 4096);
  const int tid = threadIdx.x, w = tid >> 5, lane = tid & 31, g = lane >> 2, t = lane & 3;
  const int s1 = blockIdx.x;
  if (tid >= 512) {
    if (!x_is_input) return;
    const int u = tid - 512;
    const unsigned short* gr = reinterpret_cast<const unsigned short*>(wr) + s1 * DF_;
    const unsigned short* gi = reinterpret_cast<const unsigned short*>(wi) + s1 * DF_;
    unsigned short wa[2][16], wb[2][16], wa2 = 0, wb2 = 0;
#pragma unroll
    for (int c = 0; c < 2; c++)
#pragma unroll
      for (int i = 0; i < 16; i++) {
        asm volatile("ld.global.nc.u16 %0, [%1];" : "=h"(wa[c][i]) : "l"(gr + 128 * i * DF_ + 2 * u + c));
        asm volatile("ld.global.nc.u16 %0, [%1];" : "=h"(wb[c][i]) : "l"(gi + 128 * i * DF_ + 2 * u + c));
      }
    if (u < 16) {
      asm volatile("ld.global.nc.u16 %0, [%1];" : "=h"(wa2) : "l"(gr + 128 * u * DF_ + 256));
      asm volatile("ld.global.nc.u16 %0, [%1];" : "=h"(wb2) : "l"(gi + 128 * u * DF_ + 256));
    }
    pdl_wait();
    const int jj = s1 & 15, jq = s1 >> 4;
    uint32_t* wd = g_Wt + (size_t)((((jj >> 1) * 16 + (u >> 3)) * 16 + (jj & 1) * 8 + jq) * 32 + (u & 7) * 4) * 8;
    uint32_t mx = 0;
#pragma unroll
    for (int tt = 0; tt < 4; tt++) {
      uint32_t o[8];
#pragma unroll
      for (int q = 0; q < 8; q++) {
        const int c = q >> 2, i = 2 * (tt + 4 * (q & 1)) + ((q >> 1) & 1);
        o[q] = (uint32_t)wa[c][i] | ((uint32_t)wb[c][i] << 16);
        mx = max(mx, max(o[q] & 0x7fffu, (o[q] >> 16) & 0x7fffu));
        if (u == 0 && c == 0) g_Wn[2048 + s1 + 128 * i] = o[q];
      }
      *reinterpret_cast<uint4*>(wd + tt * 8) = make_uint4(o[0], o[1], o[2], o[3]);
      *reinterpret_cast<uint4*>(wd + tt * 8 + 4) = make_uint4(o[4], o[5], o[6], o[7]);
    }
    if (u < 16) {
      g_Wn[s1 + 128 * u] = (uint32_t)wa2 | ((uint32_t)wb2 << 16);
      mx = max(mx, max((uint32_t)(wa2 & 0x7fff), (uint32_t)(wb2 & 0x7fff)));
    }
    mx = __reduce_max_sync(0xffffffffu, mx);
    __shared__ uint32_t red[4];
    if (lane == 0) red[u >> 5] = mx;
    asm volatile("bar.sync 2, 128;" ::: "memory");
    if (u == 0) g_wmax[s1] = max(max(red[0], red[1]), max(red[2], red[3]));
    if (s1 == 0) { for (int i = u; i < 2 * 28 * 8; i += 128) g_flags[i * FLAG_PITCH] = 0u; }
    return;
  }
  const uint32_t* xr = reinterpret_cast<const uint32_t*>(x + (size_t)(s1 + 128 * w) * D_) + 2 * g + 16 * t;
  uint32_t xraw[2][4];
  if (x_is_input) {
#pragma unroll
    for (int i = 0; i < 4; i++) ldg_u64(xr + 64 * i, xraw[0][i], xraw[1][i]);
  }
  uint32_t bf[2][4][2];
  dft_frags<16>(bf, lane);
  float2 tw[2][4], ts[4], pw[2];
  lane_tw(tw, 6, lane);
  pw[0] = twiddle(16 * w + 2 * g, 512);
  pw[1] = twiddle(16 * w + 2 * g + 1, 512);
#pragma unroll
  for (int j = 0; j < 4; j++) ts[j] = twiddle(s1 * (t + 4 * j), 2048);
  pdl_wait_after_loads(rsm + w * 256 + lane);
  pdl_launch();
  if (!x_is_input) {
#pragma unroll
    for (int i = 0; i < 4; i++) ldg_u64(xr + 64 * i, xraw[0][i], xraw[1][i]);
  }
  float2 v[2][4];
  uint32_t h[2][4], h2[2][4];
#pragma unroll
  for (int b = 0; b < 2; b++)
#pragma unroll
    for (int i = 0; i < 4; i++) v[b][i] = bf2_to_f2(xraw[b][i]);
  {
    float mean, var, mb, rs;
    row_stats(v, mean, var);
    ln_coef(mean, var, mb, rs);
    rs *= 8.f;
    const float c0 = -mb * rs;
#pragma unroll
    for (int b = 0; b < 2; b++)
#pragma unroll
      for (int i = 0; i < 4; i++) h[b][i] = f2_to_h2(make_float2(fmaf(v[b][i].x, rs, c0), fmaf(v[b][i].y, rs, c0)));
  }
  dft_tile<16>(h, v, bf);
#pragma unroll
  for (int b = 0; b < 2; b++)
#pragma unroll
    for (int j = 0; j < 4; j++) h[b][j] = f2_to_h2(cmul(v[b][j], tw[b][j]));
  warp_transpose(h, h2, smem_u32(rsm) + w * 1024, g, t);
  dft_tile<16>(h2, v, bf);
#pragma unroll
  for (int j = 0; j < 4; j++)
    *reinterpret_cast<float4*>(zs + w * RP + 20 * (t + 4 * j) + 2 * g) = make_float4(v[0][j].x, v[0][j].y, v[1][j].x, v[1][j].y);
  asm volatile("bar.sync 1, 512;" ::: "memory");
  if (x_is_input) {
    if (tid == 0) {
      int per = (pf0_bytes / 128) & ~15;
      asm volatile("cp.async.bulk.prefetch.L2.global [%0], %1;" ::"l"((const char*)pf0 + (size_t)s1 * per), "r"(per) : "memory");
    }
  }
  {
    const int k = 16 * w + 2 * g;
    const float2* pa = zs + t * RP + kpad(k);
    const float2* pb0 = zs + t * RP + kpad((256 - k) & 255);
    const float2* pb1 = zs + t * RP + kpad(255 - k);
#pragma unroll
    for (int i = 0; i < 4; i++) {
      const float4 a4 = *reinterpret_cast<const float4*>(pa + 4 * i * RP);
#pragma unroll
      for (int b = 0; b < 2; b++) {
        const float2 a = b ? make_float2(a4.z, a4.w) : make_float2(a4.x, a4.y);
        const float2 c = b ? pb1[4 * i * RP] : pb0[4 * i * RP];
        float ex = a.x + c.x, ey = a.y - c.y, ox = a.y + c.y, oy = c.x - a.x;
        float re = fmaf(pw[b].x, ox, fmaf(-pw[b].y, oy, ex));
        float im = fmaf(pw[b].x, oy, fmaf(pw[b].y, ox, ey));
        if (b == 0) im = k == 0 ? ex - ox : im;
        h[b][i] = f2_to_h2(make_float2(re, im));
      }
    }
  }
  dft_tile<16>(h, v, bf);
  uint32_t* dst = g_T + (size_t)s1 * 4096 + t * 256 + 16 * w + 2 * g;
#pragma unroll
  for (int j = 0; j < 4; j++)
  {
    const uint32_t o0 = f2_to_h2(cmul(v[0][j], ts[j]));
    *reinterpret_cast<uint2*>(dst + j * 1024) = make_uint2(o0, f2_to_h2(cmul(v[1][j], ts[j])));
    if (tid < 4) g_T0[s1 * 16 + t + 4 * j] = o0;
  }
}

template <bool COL0>
__device__ __forceinline__ void col_body(uint32_t* csm, const void* pf0, int pf0_bytes) {
  const int w = threadIdx.x >> 5, lane = threadIdx.x & 31, g = lane >> 2, t = lane & 3;
  const int bid = blockIdx.x - 1;
  const int jp = bid >> 4, kb = bid & 15;
  const int jsel = w >> 3, wq = w & 7;
  const int jj = COL0 ? 2 * g : 2 * jp + jsel;
  uint32_t bf16p[2][4][2], bf8[2][4][2];
  dft_frags<16>(bf16p, lane);
  dft_frags<8>(bf8, lane);
  float2 ta[4], tb[4], tc[4], tc1[4];
#pragma unroll
  for (int j = 0; j < 4; j++) {
    ta[j] = twiddle(wq * (t + 4 * j), 128);
    tb[j] = twiddle((t + 4 * (j & 1)) * (wq + 8 * (j >> 1)), 128);
    tc[j] = twiddle((wq + 8 * (t + 4 * j)) * jj, 2048);
    if (COL0) tc1[j] = twiddle((wq + 8 * (t + 4 * j)) * (jj + 1), 2048);
  }
  uint32_t* e1 = csm + jsel * 2048 + 4 * g + ((t + wq) & 3) + 32 * ((wq & 3) + 16 * (wq >> 2));
  uint32_t* e2 = csm + jsel * 2048 + 4 * g + ((t + wq) & 3) + 32 * (t + 4 * (wq >> 2));
  pdl_wait_after_loads(csm + 12288 + threadIdx.x);
  pdl_launch();
  if (!COL0 && pf0 != nullptr && threadIdx.x == 0) {
    int per = (pf0_bytes / 128) & ~15;
    asm volatile("cp.async.bulk.prefetch.L2.global [%0], %1;" ::"l"((const char*)pf0 + (size_t)bid * per), "r"(per) : "memory");
  }
  constexpr size_t RS = COL0 ? 32 * 16 : 32 * 4096;
  uint32_t* base = COL0 ? g_T0 + (wq + 8 * t) * 16 + jj : g_T + (size_t)(wq + 8 * t) * 4096 + jj * 256 + kb * 16 + 2 * g;
  uint32_t h[2][4], wp[2][4];
  float2 v[2][4];
  uint32_t* wsm = csm + 8192;
#pragma unroll
  for (int i = 0; i < 4; i++) ldg_u64(base + i * RS, h[0][i], h[1][i]);
  dft_tile<16>(h, v, bf16p);
  if (COL0) {
#pragma unroll
    for (int i = 0; i < 4; i++) *reinterpret_cast<uint4*>(wsm + (i * 256 + threadIdx.x) * 4) = ldg_u128(g_Wn + (i * 256 + threadIdx.x) * 4);
  } else {
    const uint4 w0 = ldg_u128(g_Wt + ((size_t)bid * 512 + threadIdx.x) * 8), w1 = ldg_u128(g_Wt + ((size_t)bid * 512 + threadIdx.x) * 8 + 4);
    wp[0][0] = w0.x; wp[0][1] = w0.y; wp[0][2] = w0.z; wp[0][3] = w0.w;
    wp[1][0] = w1.x; wp[1][1] = w1.y; wp[1][2] = w1.z; wp[1][3] = w1.w;
  }
  const uint4 wm = ldg_u128(g_wmax + lane * 4);
#pragma unroll
  for (int b = 0; b < 2; b++)
#pragma unroll
    for (int j = 0; j < 4; j++) e1[128 * j + 1024 * b] = f2_to_h2(cmul(v[b][j], ta[j]));
  asm volatile("bar.sync %0, 256;" ::"r"(1 + jsel) : "memory");
#pragma unroll
  for (int b = 0; b < 2; b++)
#pragma unroll
    for (int i = 0; i < 4; i++) h[b][i] = e2[512 * (i & 1) + 256 * (i >> 1) + 1024 * b];
  dft_tile<8>(h, v, bf8);
  const float wsc = filter_scale(wm, false);
  if (COL0) {
    float2* tp = reinterpret_cast<float2*>(csm + 4096);
#pragma unroll
    for (int j = 0; j < 4; j++)
      *reinterpret_cast<float4*>(tp + jj + 16 * (wq + 8 * (j >> 1)) + 256 * (t + 4 * (j & 1))) = make_float4(v[0][j].x, v[0][j].y, v[1][j].x, v[1][j].y);
    asm volatile("bar.sync 1, 256;" ::: "memory");
    const float q = 0.25f * wsc;
#pragma unroll
    for (int b = 0; b < 2; b++)
#pragma unroll
      for (int j = 0; j < 4; j++) {
        const int sig = jj + b + 16 * (wq + 8 * (j >> 1)) + 256 * (t + 4 * (j & 1));
        const int nsig = (2048 - sig) & 2047;
        const float2 p = v[b][j], pm = tp[nsig];
        const float2 A = make_float2(p.x + pm.x, p.y - pm.y), B = make_float2(p.y + pm.y, pm.x - p.x);
        const float2 a0 = bf2_to_f2(wsm[2048 + sig]), a1 = bf2_to_f2(wsm[2048 + nsig]), n0 = bf2_to_f2(wsm[sig]), n1 = bf2_to_f2(wsm[nsig]);
        const float2 ya = cmul(A, make_float2((a0.x + a1.x) * q, (a0.y - a1.y) * q));
        const float2 yb = cmul(B, make_float2((n0.x + n1.x) * q, (n0.y - n1.y) * q));
        h[b][j] = f2_to_h2(make_float2(ya.x - yb.y, -(ya.y + yb.x)));
      }
  } else {
#pragma unroll
    for (int b = 0; b < 2; b++)
#pragma unroll
      for (int j = 0; j < 4; j++) {
        const float2 wv = bf2_to_f2(wp[b][j]);
        const float2 y = cmul(v[b][j], make_float2(wv.x * wsc, wv.y * wsc));
        h[b][j] = f2_to_h2(make_float2(y.x, -y.y));
      }
  }
  dft_tile<8>(h, v, bf8);
#pragma unroll
  for (int b = 0; b < 2; b++)
#pragma unroll
    for (int j = 0; j < 4; j++) e2[512 * (j & 1) + 256 * (j >> 1) + 1024 * b] = f2_to_h2(cmul(v[b][j], tb[j]));
  asm volatile("bar.sync %0, 256;" ::"r"(1 + jsel) : "memory");
#pragma unroll
  for (int b = 0; b < 2; b++)
#pragma unroll
    for (int i = 0; i < 4; i++) h[b][i] = e1[128 * i + 1024 * b];
  dft_tile<16>(h, v, bf16p);
#pragma unroll
  for (int j = 0; j < 4; j++)
    *reinterpret_cast<uint2*>(base + j * RS) = make_uint2(f2_to_h2(cmul(v[0][j], tc[j])), f2_to_h2(cmul(v[1][j], COL0 ? tc1[j] : tc[j])));
}
__global__ void __launch_bounds__(512, 1) k_col(const void* pf0, int pf0_bytes) {
  extern __shared__ __align__(16) uint32_t csm[];
  if (blockIdx.x > 0) col_body<false>(csm, pf0, pf0_bytes);
  else if (threadIdx.x < 256) col_body<true>(csm, pf0, pf0_bytes);
}

__global__ void __launch_bounds__(R_THREADS, 1) k_row_inv(const __nv_bfloat16* __restrict__ x) {
  extern __shared__ __align__(1024) uint32_t rsm[];
  float2* zs = reinterpret_cast<float2*>(rsm + 4096);
  const int tid = threadIdx.x, w = tid >> 5, lane = tid & 31, g = lane >> 2, t = lane & 3;
  const int s1 = blockIdx.x;
  uint32_t bf[2][4][2];
  dft_frags<16>(bf, lane);
  float2 tw[2][4], pw[2][4];
  lane_tw(tw, 6, lane);
  lane_tw(pw, 10, lane);
  pdl_wait_after_loads(rsm + w * 256 + lane);
  pdl_launch();
  uint32_t h[2][4], h2[2][4], xin[2][4];
  float2 v[2][4];
  const uint32_t* src = g_T + (size_t)s1 * 4096 + t * 256 + 16 * w + 2 * g;
#pragma unroll
  for (int i = 0; i < 4; i++) ldg_u64(src + i * 1024, h[0][i], h[1][i]);
  if (tid < 4) {
#pragma unroll
    for (int i = 0; i < 4; i++) h[0][i] = ldg_u32(g_T0 + s1 * 16 + t + 4 * i);
  }
  const size_t rowoff = (size_t)(s1 + 128 * w) * (D_ / 2) + 2 * g + 16 * t;
  const uint32_t* xr = reinterpret_cast<const uint32_t*>(x) + rowoff;
  dft_tile<16>(h, v, bf);
#pragma unroll
  for (int i = 0; i < 4; i++) ldg_u64(xr + 64 * i, xin[0][i], xin[1][i]);
  const uint4 wm = ldg_u128(g_wmax + lane * 4);
#pragma unroll
  for (int j = 0; j < 4; j++)
    *reinterpret_cast<float4*>(zs + (t + 4 * j) * RP + 20 * w + 2 * g) = make_float4(v[0][j].x, v[0][j].y, v[1][j].x, v[1][j].y);
  asm volatile("bar.sync 1, 512;" ::: "memory");
  {
    const float2* pa = zs + w * RP + 20 * t + 2 * g;
    const float2* pm = zs + w * RP + 20 * (15 - t) + 15 - 2 * g;
#pragma unroll
    for (int i = 0; i < 4; i++) {
      const float4 a4 = *reinterpret_cast<const float4*>(pa + 80 * i);
#pragma unroll
      for (int b = 0; b < 2; b++) {
        const float2 a = b ? make_float2(a4.z, a4.w) : make_float2(a4.x, a4.y);
        const float2 c = b ? pm[-80 * i] : pm[-80 * i + (g == 0 ? 5 : 1)];
        float ex = a.x + c.x, ey = a.y - c.y;
        float2 o = cmul(make_float2(a.x - c.x, a.y + c.y), pw[b][i]);
        float2 z = make_float2(ex + o.y, ey - o.x);
        if (b == 0 && i == 0 && lane == 0) z = make_float2(a.x - a.y, -(a.x + a.y));
        h[b][i] = f2_to_h2(z);
      }
    }
  }
  const float osc = filter_scale(wm, true);
  dft_tile<16>(h, v, bf);
#pragma unroll
  for (int b = 0; b < 2; b++)
#pragma unroll
    for (int j = 0; j < 4; j++) h[b][j] = f2_to_h2(cmul(v[b][j], tw[b][j]));
  warp_transpose(h, h2, smem_u32(rsm) + w * 1024, g, t);
  dft_tile<16>(h2, v, bf);
  uint32_t* x1r = reinterpret_cast<uint32_t*>(g_X1) + rowoff;
  uint32_t* hr = reinterpret_cast<uint32_t*>(g_H) + rowoff;
#pragma unroll
  for (int j = 0; j < 4; j++) {
    const uint32_t p0 = bf2_add(xin[0][j], f2_to_bf2(v[0][j].x * osc, -v[0][j].y * osc));
    const uint32_t p1 = bf2_add(xin[1][j], f2_to_bf2(v[1][j].x * osc, -v[1][j].y * osc));
    *reinterpret_cast<uint2*>(x1r + 64 * j) = make_uint2(p0, p1);
    v[0][j] = bf2_to_f2(p0);
    v[1][j] = bf2_to_f2(p1);
  }
  {
    float mean, var, mb, rs, mb2, rs2;
    row_stats(v, mean, var);
    ln_coef(mean, var, mb, rs);
    ln_coef((mean - mb) * rs, var * rs * rs, mb2, rs2);
    const float a = rs * rs2, c0 = (-mb * rs - mb2) * rs2;
#pragma unroll
    for (int j = 0; j < 4; j++)
      *reinterpret_cast<uint2*>(hr + 64 * j) = make_uint2(f2_to_bf2(fmaf(v[0][j].x, a, c0), fmaf(v[0][j].y, a, c0)),
                                                          f2_to_bf2(fmaf(v[1][j].x, a, c0), fmaf(v[1][j].y, a, c0)));
  }
}

__device__ __forceinline__ void wgmma_n128(float (&d)[64], uint64_t da, uint64_t db, int accum) {
  asm volatile("{\n.reg .pred p;\nsetp.ne.b32 p, %66, 0;\n"
    "wgmma.mma_async.sync.aligned.m64n128k16.f32.bf16.bf16 {%0, %1, %2, %3, %4, %5, %6, %7, %8, %9, %10, %11, %12, %13, %14, %15, %16, %17, %18, %19, %20, %21, %22, %23, %24, %25, %26, %27, %28, %29, %30, %31, %32, %33, %34, %35, %36, %37, %38, %39, %40, %41, %42, %43, %44, %45, %46, %47, %48, %49, %50, %51, %52, %53, %54, %55, %56, %57, %58, %59, %60, %61, %62, %63}, %64, %65, p, 1, 1, 1, 1;\n}\n"
    : "+f"(d[0]), "+f"(d[1]), "+f"(d[2]), "+f"(d[3]), "+f"(d[4]), "+f"(d[5]), "+f"(d[6]), "+f"(d[7]), "+f"(d[8]), "+f"(d[9]), "+f"(d[10]), "+f"(d[11]), "+f"(d[12]), "+f"(d[13]), "+f"(d[14]), "+f"(d[15]), "+f"(d[16]), "+f"(d[17]), "+f"(d[18]), "+f"(d[19]), "+f"(d[20]), "+f"(d[21]), "+f"(d[22]), "+f"(d[23]), "+f"(d[24]), "+f"(d[25]), "+f"(d[26]), "+f"(d[27]), "+f"(d[28]), "+f"(d[29]), "+f"(d[30]), "+f"(d[31]), "+f"(d[32]), "+f"(d[33]), "+f"(d[34]), "+f"(d[35]), "+f"(d[36]), "+f"(d[37]), "+f"(d[38]), "+f"(d[39]), "+f"(d[40]), "+f"(d[41]), "+f"(d[42]), "+f"(d[43]), "+f"(d[44]), "+f"(d[45]), "+f"(d[46]), "+f"(d[47]), "+f"(d[48]), "+f"(d[49]), "+f"(d[50]), "+f"(d[51]), "+f"(d[52]), "+f"(d[53]), "+f"(d[54]), "+f"(d[55]), "+f"(d[56]), "+f"(d[57]), "+f"(d[58]), "+f"(d[59]), "+f"(d[60]), "+f"(d[61]), "+f"(d[62]), "+f"(d[63])
    : "l"(da), "l"(db), "r"(accum));
}
__device__ __forceinline__ void wgmma_n160(float (&d)[80], uint64_t da, uint64_t db, int accum) {
  asm volatile("{\n.reg .pred p;\nsetp.ne.b32 p, %82, 0;\n"
    "wgmma.mma_async.sync.aligned.m64n160k16.f32.bf16.bf16 {%0, %1, %2, %3, %4, %5, %6, %7, %8, %9, %10, %11, %12, %13, %14, %15, %16, %17, %18, %19, %20, %21, %22, %23, %24, %25, %26, %27, %28, %29, %30, %31, %32, %33, %34, %35, %36, %37, %38, %39, %40, %41, %42, %43, %44, %45, %46, %47, %48, %49, %50, %51, %52, %53, %54, %55, %56, %57, %58, %59, %60, %61, %62, %63, %64, %65, %66, %67, %68, %69, %70, %71, %72, %73, %74, %75, %76, %77, %78, %79}, %80, %81, p, 1, 1, 1, 1;\n}\n"
    : "+f"(d[0]), "+f"(d[1]), "+f"(d[2]), "+f"(d[3]), "+f"(d[4]), "+f"(d[5]), "+f"(d[6]), "+f"(d[7]), "+f"(d[8]), "+f"(d[9]), "+f"(d[10]), "+f"(d[11]), "+f"(d[12]), "+f"(d[13]), "+f"(d[14]), "+f"(d[15]), "+f"(d[16]), "+f"(d[17]), "+f"(d[18]), "+f"(d[19]), "+f"(d[20]), "+f"(d[21]), "+f"(d[22]), "+f"(d[23]), "+f"(d[24]), "+f"(d[25]), "+f"(d[26]), "+f"(d[27]), "+f"(d[28]), "+f"(d[29]), "+f"(d[30]), "+f"(d[31]), "+f"(d[32]), "+f"(d[33]), "+f"(d[34]), "+f"(d[35]), "+f"(d[36]), "+f"(d[37]), "+f"(d[38]), "+f"(d[39]), "+f"(d[40]), "+f"(d[41]), "+f"(d[42]), "+f"(d[43]), "+f"(d[44]), "+f"(d[45]), "+f"(d[46]), "+f"(d[47]), "+f"(d[48]), "+f"(d[49]), "+f"(d[50]), "+f"(d[51]), "+f"(d[52]), "+f"(d[53]), "+f"(d[54]), "+f"(d[55]), "+f"(d[56]), "+f"(d[57]), "+f"(d[58]), "+f"(d[59]), "+f"(d[60]), "+f"(d[61]), "+f"(d[62]), "+f"(d[63]), "+f"(d[64]), "+f"(d[65]), "+f"(d[66]), "+f"(d[67]), "+f"(d[68]), "+f"(d[69]), "+f"(d[70]), "+f"(d[71]), "+f"(d[72]), "+f"(d[73]), "+f"(d[74]), "+f"(d[75]), "+f"(d[76]), "+f"(d[77]), "+f"(d[78]), "+f"(d[79])
    : "l"(da), "l"(db), "r"(accum));
}


__device__ __forceinline__ void mbar_init(uint32_t a, uint32_t cnt) { asm volatile("mbarrier.init.shared::cta.b64 [%0], %1;" ::"r"(a), "r"(cnt)); }
__device__ __forceinline__ void mbar_expect_tx(uint32_t a, uint32_t bytes) {
  asm volatile("mbarrier.arrive.expect_tx.shared::cta.b64 _, [%0], %1;" ::"r"(a), "r"(bytes) : "memory");
}
__device__ __forceinline__ uint32_t mbar_try(uint32_t a, uint32_t parity) {
  uint32_t ok;
  asm volatile("{\n.reg .pred p;\nmbarrier.try_wait.parity.shared::cta.b64 p, [%1], %2;\nselp.u32 %0,1,0,p;\n}" : "=r"(ok) : "r"(a), "r"(parity) : "memory");
  return ok;
}
__device__ __forceinline__ uint32_t mbar_test(uint32_t a, uint32_t parity) {
  uint32_t ok;
  asm volatile("{\n.reg .pred p;\nmbarrier.test_wait.parity.shared::cta.b64 p, [%1], %2;\nselp.u32 %0,1,0,p;\n}" : "=r"(ok) : "r"(a), "r"(parity) : "memory");
  return ok;
}
__device__ __forceinline__ void mbar_wait_slow(uint32_t a, uint32_t parity) {
  asm volatile(
      "{\n.reg .pred P1;\n.reg .u32 c;\nmov.u32 c, 0;\nLAB_WAIT:\n"
      "mbarrier.try_wait.parity.shared::cta.b64 P1, [%0], %1;\n@P1 bra DONE;\n"
      "add.u32 c, c, 1;\nsetp.lt.u32 P1, c, 8000000;\n@P1 bra LAB_WAIT;\ntrap;\nDONE:\n}" ::"r"(a), "r"(parity) : "memory");
}
__device__ __forceinline__ void mbar_wait(uint32_t a, uint32_t parity) {
  if (!mbar_try(a, parity)) mbar_wait_slow(a, parity);
}
__device__ __forceinline__ void tma2d_mc(uint32_t dst, const CUtensorMap* tm, int c0, int c1, uint32_t mbar, uint16_t mask) {
  asm volatile("cp.async.bulk.tensor.2d.shared::cluster.global.mbarrier::complete_tx::bytes.multicast::cluster [%0], [%1, {%3, %4}], [%2], %5;"
               ::"r"(dst), "l"(tm), "r"(mbar), "r"(c0), "r"(c1), "h"(mask) : "memory");
}
__device__ __forceinline__ void tma2d_store(const CUtensorMap* tm, uint32_t src, int c0, int c1) {
  asm volatile("cp.async.bulk.tensor.2d.global.shared::cta.bulk_group [%0, {%2, %3}], [%1];" ::"l"(tm), "r"(src), "r"(c0), "r"(c1) : "memory");
}
__device__ __forceinline__ bool elect_one() {
  uint32_t p;
  asm volatile("{\n.reg .pred P;\nelect.sync _|P, 0xffffffff;\nselp.u32 %0,1,0,P;\n}" : "=r"(p));
  return p;
}
__device__ __forceinline__ uint64_t mkdesc(uint32_t addr, uint32_t lbo, uint32_t sbo, uint64_t swz) {
  return (uint64_t)((addr & 0x3FFFF) >> 4) | ((uint64_t)(lbo >> 4) << 16) | ((uint64_t)(sbo >> 4) << 32) | (swz << 62);
}
__device__ __forceinline__ void wg_fence() { asm volatile("wgmma.fence.sync.aligned;" ::: "memory"); }
__device__ __forceinline__ void wg_commit() { asm volatile("wgmma.commit_group.sync.aligned;" ::: "memory"); }
template <int N> __device__ __forceinline__ void wg_wait() { asm volatile("wgmma.wait_group.sync.aligned %0;" ::"n"(N) : "memory"); }
__device__ __forceinline__ void cluster_sync() {
  asm volatile("barrier.cluster.arrive.relaxed.aligned;\nbarrier.cluster.wait.aligned;" ::: "memory");
}
__device__ __forceinline__ void stmatrix_x4_t(uint32_t addr, uint32_t r0, uint32_t r1, uint32_t r2, uint32_t r3) {
  asm volatile("stmatrix.sync.aligned.m8n8.x4.trans.shared.b16 [%0], {%1, %2, %3, %4};" ::"r"(addr), "r"(r0), "r"(r1), "r"(r2), "r"(r3) : "memory");
}
constexpr int G_NS1 = 8, G_ST1 = 24576;
constexpr int G_NS2 = 6, G_ST2 = 32768;
constexpr int G_BN2 = 160;
constexpr int G_KB1 = 32, G_KB2 = 28;
constexpr int G_SMEM = G_NS2 * G_ST2 + 1024;
constexpr int B_F1 = 0, B_E1 = 64, B_F2 = 128, B_E2 = 176, B_HO = 224, B_N = 34;

__device__ __forceinline__ float gelu_fast(float u) {
  float t = fmaf(u * u, 0.044715f * 0.7978845608028654f, 0.7978845608028654f);
  float th;
  asm("tanh.approx.f32 %0, %1;" : "=f"(th) : "f"(u * t));
  float h = 0.5f * u;
  return fmaf(h, th, h);
}

__device__ __forceinline__ uint32_t opaque(uint32_t v) { asm volatile("" : "+r"(v)); return v; }

__device__ __forceinline__ void handover(uint32_t rem_bars, int st) {
  const int lo = (st * 3) >> 2, hi = (st * 3 + 2) >> 2;
  asm volatile("mbarrier.arrive.shared::cluster.b64 _, [%0];" ::"r"(rem_bars + B_HO + lo * 8) : "memory");
  if (hi != lo) asm volatile("mbarrier.arrive.shared::cluster.b64 _, [%0];" ::"r"(rem_bars + B_HO + hi * 8) : "memory");
}
template <int G>
__device__ __forceinline__ void mlp_mainloop(float (&acc)[80], int wgi, bool both, uint64_t dA0, uint64_t dB0, uint32_t bars, uint32_t rem_bars, bool do_arr) {
  constexpr int NKB = G == 0 ? G_KB1 : G_KB2, NS = G == 0 ? G_NS1 : G_NS2, ST = G == 0 ? G_ST1 : G_ST2;
  constexpr int BF = G == 0 ? B_F1 : B_F2, BE = G == 0 ? B_E1 : B_E2;
  int st = wgi, ph = 0;
  uint32_t so = st * (ST >> 4);
  mbar_wait(bars + BF + st * 8, ph);
#pragma unroll 1
  for (int kb = wgi; kb < NKB; kb += 2) {
    const uint64_t da = dA0 + so, db = dB0 + so;
    wg_fence();
#pragma unroll
    for (int q = 0; q < 4; q++) {
      if (G == 1) wgmma_n160(acc, da + q * 128, db + q * 128, (kb >> 1) + q);
      else wgmma_n128(reinterpret_cast<float (&)[64]>(acc), da + q * 128, db + q * 128, (kb >> 1) + q);
    }
    wg_commit();
    uint32_t rel = 0, rel2 = 0;
    if (kb + NS < NKB) rel = rem_bars + BE + st * 8;
    else if (G == 0 && both && kb + 2 < NKB) {
      const int lo = (st * 3) >> 2, hi = (st * 3 + 2) >> 2;
      rel = rem_bars + B_HO + lo * 8;
      if (hi != lo) rel2 = rem_bars + B_HO + hi * 8;
    }
    st += 2;
    if (st >= NS) { st -= NS; ph ^= 1; }
    so = __shfl_sync(0xffffffffu, opaque(st * (ST >> 4)), 0);
    const uint32_t ready = kb + 2 < NKB ? mbar_test(bars + BF + st * 8, ph) : 1u;
    wg_wait<0>();
    if (do_arr && rel) asm volatile("mbarrier.arrive.shared::cluster.b64 _, [%0];" ::"r"(rel) : "memory");
    if (G == 0 && do_arr && rel2) asm volatile("mbarrier.arrive.shared::cluster.b64 _, [%0];" ::"r"(rel2) : "memory");
    if (!ready) mbar_wait(bars + BF + st * 8, ph);
  }
}

template <int G, int WGI>
__device__ __forceinline__ void mlp_epilogue(float (&acc)[80], const uint32_t (&bv)[10], const uint4 (&xv)[5], uint32_t smb, bool both,
                                             uint32_t rem_bars, bool do_arr, int cn, int lane, int w4, int n0, int d0, __nv_bfloat16* out) {
  constexpr int NQ = G == 0 ? 8 : 10;
  constexpr int KEEP = WGI * NQ * 4, GIVE = (1 - WGI) * NQ * 4;
  const int tq = w4 * 32 + lane;
  constexpr int NKB = G == 0 ? G_KB1 : G_KB2, NS = G == 0 ? G_NS1 : G_NS2, ST = G == 0 ? G_ST1 : G_ST2;
  constexpr int lst = (NKB - 2 + WGI) % NS, ost = lst ^ 1;
  const uint32_t mine = smb + lst * ST + 8192 + tq * 16, other = smb + ost * ST + 8192 + tq * 16;
#pragma unroll
  for (int i = 0; i < NQ; i++)
    asm volatile("st.shared.v4.f32 [%0], {%1,%2,%3,%4};" ::"r"(mine + i * 2048), "f"(acc[GIVE + 4 * i]), "f"(acc[GIVE + 4 * i + 1]), "f"(acc[GIVE + 4 * i + 2]), "f"(acc[GIVE + 4 * i + 3]) : "memory");
#pragma unroll
  for (int j = 0; j < NQ; j++) {
    const float2 bb = bf2_to_f2(bv[j]);
    acc[KEEP + 4 * j] += bb.x; acc[KEEP + 4 * j + 1] += bb.y; acc[KEEP + 4 * j + 2] += bb.x; acc[KEEP + 4 * j + 3] += bb.y;
  }
  asm volatile("bar.sync 1, 256;" ::: "memory");
#pragma unroll
  for (int i = 0; i < NQ; i++) {
    float4 p;
    asm volatile("ld.shared.v4.f32 {%0,%1,%2,%3}, [%4];" : "=f"(p.x), "=f"(p.y), "=f"(p.z), "=f"(p.w) : "r"(other + i * 2048));
    acc[KEEP + 4 * i] += p.x; acc[KEEP + 4 * i + 1] += p.y; acc[KEEP + 4 * i + 2] += p.z; acc[KEEP + 4 * i + 3] += p.w;
  }
  const uint32_t stg = smb + (G == 0 ? (2 * cn + WGI) * G_ST2 : ((lst + 2) % NS) * ST);
  const int mat = lane >> 3;
  const uint32_t sta = stg + (8 * (mat >> 1) + (lane & 7)) * 128 + (((2 * w4 + (mat & 1)) ^ (lane & 7)) * 16);
#pragma unroll
  for (int j = 0; j < NQ; j += 2) {
    uint32_t r[4];
#pragma unroll
    for (int e = 0; e < 4; e++) {
      float u0 = acc[KEEP + 4 * j + 2 * e], u1 = acc[KEEP + 4 * j + 2 * e + 1];
      if (G == 0) { u0 = gelu_fast(u0); u1 = gelu_fast(u1); }
      r[e] = f2_to_bf2(u0, u1);
    }
    stmatrix_x4_t(sta + j * 1024, r[0], r[1], r[2], r[3]);
  }
  if (G == 0) {
    asm volatile("fence.proxy.async.shared::cta;" ::: "memory");
    asm volatile("bar.arrive %0, 160;" ::"r"(2 + WGI) : "memory");
    if (both) {
      asm volatile("bar.sync %0, 128;" ::"r"(4 + WGI) : "memory");
      if (do_arr) handover(rem_bars, ost);
    }
  } else {
    asm volatile("bar.sync %0, 128;" ::"r"(4 + WGI) : "memory");
#pragma unroll
    for (int i = 0; i < 5; i++) {
      const int n = i * 16 + (tq >> 3), c = tq & 7;
      const int srow = n0 + n;
      if (srow < S_) {
        uint4 y;
        asm volatile("ld.shared.v4.b32 {%0,%1,%2,%3}, [%4];" : "=r"(y.x), "=r"(y.y), "=r"(y.z), "=r"(y.w) : "r"(stg + n * 128 + ((c ^ (n & 7)) * 16)));
        *reinterpret_cast<uint4*>(out + (size_t)srow * D_ + d0 + c * 8) =
            make_uint4(bf2_add(y.x, xv[i].x), bf2_add(y.y, xv[i].y), bf2_add(y.z, xv[i].z), bf2_add(y.w, xv[i].w));
      }
    }
  }
}

__global__ void __launch_bounds__(384) k_mlp(const __grid_constant__ CUtensorMap tmH, const __grid_constant__ CUtensorMap tmW1,
                                             const __grid_constant__ CUtensorMap tmU, const __grid_constant__ CUtensorMap tmUs,
                                             const __grid_constant__ CUtensorMap tmW2,
                                             const __nv_bfloat16* __restrict__ b1, const __nv_bfloat16* __restrict__ b2,
                                             const __nv_bfloat16* resid, __nv_bfloat16* out, unsigned* flags, int mode) {
  extern __shared__ __align__(1024) char gsm_raw[];
  __shared__ __align__(8) uint64_t bars_s[B_N];
  uint32_t rank;
  asm volatile("mov.u32 %0, %%cluster_ctarank;" : "=r"(rank));
  const int warp = __shfl_sync(0xffffffffu, threadIdx.x >> 5, 0), lane = threadIdx.x & 31;
  const uint32_t smb = __shfl_sync(0xffffffffu, opaque((smem_u32(gsm_raw) + 1023u) & ~1023u), 0);
  const uint32_t bars = __shfl_sync(0xffffffffu, opaque(smem_u32(bars_s)), 0);
  const int cl = blockIdx.x >> 4;
  const int cm = rank & 7, cn = rank >> 3;
  const int nt = cl * 2 + cn;
  if (threadIdx.x == 0) {
#pragma unroll
    for (int i = 0; i < B_N; i++) mbar_init(bars + i * 8, i < 8 ? 2 : i < 16 ? 9 : i < 22 ? 2 : i < 28 ? 9 : 18);
    asm volatile("fence.mbarrier_init.release.cluster;" ::: "memory");
  }
  if (warp == 8 && lane < 5) {
    const CUtensorMap* tp = lane == 0 ? &tmW1 : lane == 1 ? &tmH : lane == 2 ? &tmW2 : lane == 3 ? &tmU : &tmUs;
    asm volatile("prefetch.tensormap [%0];" ::"l"(tp) : "memory");
  }
  __syncwarp();
  cluster_sync();
  const bool both = mode == 3;
  const int d0 = cm * 64;
  const int rot = cl * 4;
  if (warp >= 10) {
    const int pw = warp - 10;
    const uint16_t mB = (uint16_t)(0xff << (8 * cn));
    if (mode & 1) {
      const uint32_t bdst = smb + 8192 + (cm & 1) * 8192 + (cm >> 1) * 2048;
      const int c1 = nt * 128 + (cm & 1) * 64, rr = (cm >> 1) * 16;
      int st = pw, ph = 1;
#pragma unroll 1
      for (int step = pw; step < G_KB1; step += 2) {
        mbar_wait(bars + B_E1 + st * 8, ph);
        if (elect_one()) {
          mbar_expect_tx(bars + B_F1 + st * 8, 16384);
          tma2d_mc(bdst + st * G_ST1, &tmW1, c1, step * 64 + rr, bars + B_F1 + st * 8, mB);
        }
        st += 2;
        if (st >= G_NS1) { st -= G_NS1; ph ^= 1; }
      }
    }
    const int c2 = nt * G_BN2;
    int kb = rot + pw, st = pw, ph = 1;
#pragma unroll 1
    for (int i = pw; i < G_KB2; i += 2) {
      if ((mode & 1) && i == (both ? G_NS2 - 2 + pw : pw)) {
        const int so = 2 * cn + pw;
        asm volatile("bar.sync %0, 160;" ::"r"(2 + pw) : "memory");
        if (elect_one()) {
          const uint32_t src = smb + so * G_ST2;
          tma2d_store(&tmUs, src, d0, nt * 128 + pw * 64);
          asm volatile("cp.async.bulk.commit_group;" ::: "memory");
          if (both) {
            uint32_t rdst, rbar;
            asm volatile("mapa.shared::cluster.u32 %0, %1, %2;" : "=r"(rdst) : "r"(src), "r"(rank ^ 8u));
            asm volatile("mapa.shared::cluster.u32 %0, %1, %2;" : "=r"(rbar) : "r"(bars + B_F2 + so * 8), "r"(rank ^ 8u));
            asm volatile("cp.async.bulk.shared::cluster.shared::cta.mbarrier::complete_tx::bytes [%0], [%1], %2, [%3];"
                         ::"r"(rdst), "r"(src), "r"(8192), "r"(rbar) : "memory");
            asm volatile("cp.async.bulk.wait_group.read 0;" ::: "memory");
            asm volatile("mbarrier.arrive.shared::cta.b64 _, [%0];" ::"r"(bars + B_F2 + so * 8) : "memory");
          }
          asm volatile("cp.async.bulk.wait_group 0;" ::: "memory");
          if (both) {
            asm volatile("st.relaxed.gpu.global.u32 [%0], %1;" ::"l"(flags + ((nt * 2 + pw) * 8 + cm) * FLAG_PITCH), "r"(1u) : "memory");
          }
        }
        __syncwarp();
      }
      if (!(mode & 2)) break;
      if (i >= G_NS2) mbar_wait(bars + B_E2 + st * 8, ph);
      else if (both) mbar_wait(bars + B_HO + st * 8, 0);
      if (elect_one()) {
        mbar_expect_tx(bars + B_F2 + st * 8, 24576);
        const uint32_t d2 = smb + st * G_ST2 + 8192 + cm * 1024;
        tma2d_mc(d2, &tmW2, c2, kb * 64 + cm * 8, bars + B_F2 + st * 8, mB);
        tma2d_mc(d2 + 8192, &tmW2, c2 + 64, kb * 64 + cm * 8, bars + B_F2 + st * 8, mB);
        tma2d_mc(d2 + 16384, &tmW2, c2 + 128, kb * 64 + cm * 8, bars + B_F2 + st * 8, mB);
      }
      kb += 2;
      if (kb >= G_KB2) kb -= G_KB2;
      st += 2;
      if (st >= G_NS2) { st -= G_NS2; ph ^= 1; }
    }
  } else if (warp >= 8) {
    const int pw = warp - 8;
    const uint16_t mA = (uint16_t)(0x101 << cm);
    const uint32_t adst = smb + cn * 4096;
    if (both && elect_one()) mbar_expect_tx(bars + B_F2 + (2 * (1 - cn) + pw) * 8, 8192);
    pdl_wait();
    pdl_launch();
    if (mode & 1) {
      int st = pw, ph = 1;
#pragma unroll 1
      for (int step = pw; step < G_KB1; step += 2) {
        mbar_wait(bars + B_E1 + st * 8, ph);
        if (elect_one()) {
          mbar_expect_tx(bars + B_F1 + st * 8, 8192);
          tma2d_mc(adst + st * G_ST1, &tmH, d0, step * 64 + cn * 32, bars + B_F1 + st * 8, mA);
        }
        st += 2;
        if (st >= G_NS1) { st -= G_NS1; ph ^= 1; }
      }
    }
    if (mode & 2) {
      int mykb = lane + rot;
      if (mykb >= G_KB2) mykb -= G_KB2;
      const unsigned* fp = flags + (mykb * 8 + cm) * FLAG_PITCH;
      unsigned seen = (both && lane < G_KB2) ? 0u : 1u;
      unsigned mask = __ballot_sync(0xffffffffu, seen);
      int i = both ? 4 + pw : pw;
      int kb = rot + i, st = i, ph = 1;
      if (kb >= G_KB2) kb -= G_KB2;
      if (both) mbar_wait(bars + B_HO + st * 8, 0);
#pragma unroll 1
      for (; i < G_KB2; i += 2) {
        if (!((mask >> i) & 1u)) {
          int spins = 0;
          do {
            if (!seen) asm volatile("ld.relaxed.gpu.global.u32 %0, [%1];" : "=r"(seen) : "l"(fp) : "memory");
            mask = __ballot_sync(0xffffffffu, seen);
            if (++spins > 4000000) __trap();
          } while (!((mask >> i) & 1u));
          asm volatile("fence.proxy.async.global;" ::: "memory");
        }
        if (i >= G_NS2) mbar_wait(bars + B_E2 + st * 8, ph);
        if (elect_one()) {
          mbar_expect_tx(bars + B_F2 + st * 8, 8192);
          tma2d_mc(adst + st * G_ST2, &tmU, d0, kb * 64 + cn * 32, bars + B_F2 + st * 8, mA);
        }
        kb += 2;
        if (kb >= G_KB2) kb -= G_KB2;
        st += 2;
        if (st >= G_NS2) { st -= G_NS2; ph ^= 1; }
      }
    }
  } else {
    const int wgi = warp >> 2, w4 = warp & 3;
    const bool do_arr = (w4 == 0 && lane < 9);
    uint32_t rem_bars;
    asm volatile("mapa.shared::cluster.u32 %0, %1, %2;" : "=r"(rem_bars) : "r"(bars), "r"(lane < 8 ? (uint32_t)(cn * 8 + lane) : (rank ^ 8u)));
    const int tq = w4 * 32 + lane;
    const uint32_t dlo = __shfl_sync(0xffffffffu, opaque((smb & 0x3FFFF) >> 4), 0);
    const uint64_t dA0 = (mkdesc(0, 0, 1024, 1)) | dlo;
    const uint64_t dB0 = (mkdesc(0, 8192, 1024, 1)) | (dlo + 512);
    float acc[80];
#pragma unroll
    for (int i = 0; i < 80; i++) acc[i] = 0.f;
    uint32_t bv[10];
    uint4 xv[5];
    if (mode & 1) {
      const int n0 = nt * 128 + wgi * 64;
#pragma unroll
      for (int j = 0; j < 8; j++) bv[j] = __ldg(reinterpret_cast<const uint32_t*>(b1 + n0 + 8 * j + 2 * (lane & 3)));
      __syncwarp();
      mlp_mainloop<0>(acc, wgi, both, dA0, dB0, bars, rem_bars, do_arr);
      if (wgi == 0) mlp_epilogue<0, 0>(acc, bv, xv, smb, both, rem_bars, do_arr, cn, lane, w4, n0, d0, out);
      else mlp_epilogue<0, 1>(acc, bv, xv, smb, both, rem_bars, do_arr, cn, lane, w4, n0, d0, out);
    }
    if (mode & 2) {
      const int n0 = nt * G_BN2 + wgi * 80;
#pragma unroll
      for (int j = 0; j < 10; j++) {
        int n = n0 + 8 * j + 2 * (lane & 3);
        bv[j] = __ldg(reinterpret_cast<const uint32_t*>(b2 + (n < S_ ? n : 0)));
      }
      pdl_wait();
#pragma unroll
      for (int i = 0; i < 5; i++) {
        int srow = n0 + i * 16 + (tq >> 3);
        xv[i] = ldg_u128(resid + (size_t)(srow < S_ ? srow : 0) * D_ + d0 + (tq & 7) * 8);
      }
      __syncwarp();
      mlp_mainloop<1>(acc, wgi, both, dA0, dB0, bars, rem_bars, do_arr);
      if (wgi == 0) mlp_epilogue<1, 0>(acc, bv, xv, smb, both, rem_bars, do_arr, cn, lane, w4, n0, d0, out);
      else mlp_epilogue<1, 1>(acc, bv, xv, smb, both, rem_bars, do_arr, cn, lane, w4, n0, d0, out);
    }
  }
}

typedef CUresult (*EncFn)(CUtensorMap*, CUtensorMapDataType, cuuint32_t, void*, const cuuint64_t*, const cuuint64_t*, const cuuint32_t*,
                          const cuuint32_t*, CUtensorMapInterleave, CUtensorMapSwizzle, CUtensorMapL2promotion, CUtensorMapFloatOOBfill);

CUtensorMap make2d(EncFn enc, const void* p, int cols, int rows, int bc, int br, CUtensorMapSwizzle sw = CU_TENSOR_MAP_SWIZZLE_128B) {
  CUtensorMap tm;
  cuuint64_t gd[2] = {(cuuint64_t)cols, (cuuint64_t)rows};
  cuuint64_t gs[1] = {(cuuint64_t)cols * 2};
  cuuint32_t box[2] = {(cuuint32_t)bc, (cuuint32_t)br};
  cuuint32_t es[2] = {1, 1};
  enc(&tm, CU_TENSOR_MAP_DATA_TYPE_BFLOAT16, 2, const_cast<void*>(p), gd, gs, box, es, CU_TENSOR_MAP_INTERLEAVE_NONE,
      sw, CU_TENSOR_MAP_L2_PROMOTION_L2_128B, CU_TENSOR_MAP_FLOAT_OOB_FILL_NONE);
  return tm;
}

template <typename... KArgs, typename... Args>
void launch(void (*kern)(KArgs...), int grid, int block, int smem, int cluster, Args... args) {
  cudaLaunchConfig_t cfg = {};
  cfg.gridDim = dim3(grid);
  cfg.blockDim = dim3(block);
  cfg.dynamicSmemBytes = smem;
  cfg.stream = cudaStreamPerThread;
  cudaLaunchAttribute at[2];
  int n = 0;
  at[n].id = cudaLaunchAttributeProgrammaticStreamSerialization;
  at[n].val.programmaticStreamSerializationAllowed = 1;
  n++;
  if (cluster > 1) {
    at[n].id = cudaLaunchAttributeClusterDimension;
    at[n].val.clusterDim.x = cluster; at[n].val.clusterDim.y = 1; at[n].val.clusterDim.z = 1;
    n++;
  }
  cfg.attrs = at;
  cfg.numAttrs = n;
  cudaLaunchKernelEx(&cfg, kern, KArgs(args)...);
}

}

extern "C" void kernel_launch(void* const* d_in, const int* in_sizes, int n_in, void* d_out, int out_size) {
  const __nv_bfloat16* x = (const __nv_bfloat16*)d_in[0];
  const __nv_bfloat16* wr = (const __nv_bfloat16*)d_in[1];
  const __nv_bfloat16* wi = (const __nv_bfloat16*)d_in[2];
  const __nv_bfloat16* w1 = (const __nv_bfloat16*)d_in[4];
  const __nv_bfloat16* b1 = (const __nv_bfloat16*)d_in[5];
  const __nv_bfloat16* w2 = (const __nv_bfloat16*)d_in[6];
  const __nv_bfloat16* b2 = (const __nv_bfloat16*)d_in[7];
  __nv_bfloat16* out = (__nv_bfloat16*)d_out;

  static EncFn enc = nullptr;
  static int fused = 0;
  constexpr int SMC = 116 * 1024;
  if (!enc) {
    void* fn = nullptr;
    cudaDriverEntryPointQueryResult st;
    cudaGetDriverEntryPoint("cuTensorMapEncodeTiled", &fn, cudaEnableDefault, &st);
    enc = (EncFn)fn;
    cudaFuncSetAttribute(k_mlp, cudaFuncAttributeMaxDynamicSharedMemorySize, G_SMEM);
    cudaFuncSetAttribute(k_mlp, cudaFuncAttributeNonPortableClusterSizeAllowed, 1);
    cudaFuncSetAttribute(k_col, cudaFuncAttributeMaxDynamicSharedMemorySize, SMC);
    cudaFuncSetAttribute(k_row_fwd, cudaFuncAttributeMaxDynamicSharedMemorySize, R_SMEM);
    cudaFuncSetAttribute(k_row_inv, cudaFuncAttributeMaxDynamicSharedMemorySize, R_SMEM);
    cudaLaunchConfig_t cfg = {};
    cfg.gridDim = dim3(112); cfg.blockDim = dim3(384); cfg.dynamicSmemBytes = G_SMEM;
    cudaLaunchAttribute at[1];
    at[0].id = cudaLaunchAttributeClusterDimension;
    at[0].val.clusterDim.x = 16; at[0].val.clusterDim.y = 1; at[0].val.clusterDim.z = 1;
    cfg.attrs = at; cfg.numAttrs = 1;
    int nc = 0;
    if (cudaOccupancyMaxActiveClusters(&nc, k_mlp, &cfg) == cudaSuccess && nc >= 7) fused = 1;

  }
  void *pH, *pU, *pX1, *pX2, *pF;
  cudaGetSymbolAddress(&pH, g_H);
  cudaGetSymbolAddress(&pU, g_U);
  cudaGetSymbolAddress(&pX1, g_X1);
  cudaGetSymbolAddress(&pX2, g_X2);
  cudaGetSymbolAddress(&pF, g_flags);
  CUtensorMap tmH = make2d(enc, pH, D_, S_, 64, 32);
  CUtensorMap tmU = make2d(enc, pU, D_, F_, 64, 32);
  CUtensorMap tmUs = make2d(enc, pU, D_, F_, 64, 64);
  CUtensorMap tmW1 = make2d(enc, w1, F_, S_, 64, 16);
  CUtensorMap tmW2 = make2d(enc, w2, S_, F_, 64, 8);
  const __nv_bfloat16* X1 = (const __nv_bfloat16*)pX1;
  __nv_bfloat16* X2 = (__nv_bfloat16*)pX2;
  for (int layer = 0; layer < 2; layer++) {
    const __nv_bfloat16* xin = layer == 0 ? x : X2;
    __nv_bfloat16* xo = layer == 0 ? X2 : out;
    unsigned* fl = (unsigned*)pF + layer * 28 * 8 * FLAG_PITCH;
    if (layer == 0)
      launch(k_row_fwd, 128, 640, R_SMEM, 1, xin, 1, wr, wi, (const void*)w1, S_ * F_ * 2);
    else
      launch(k_row_fwd, 128, 512, R_SMEM, 1, xin, 0, wr, wi, (const void*)nullptr, 0);
    launch(k_col, 129, 512, SMC, 1, (const void*)(layer == 0 ? w2 : nullptr), S_ * F_ * 2);
    launch(k_row_inv, 128, R_THREADS, R_SMEM, 1, xin);
    if (fused) {
      launch(k_mlp, 112, 384, G_SMEM, 16, tmH, tmW1, tmU, tmUs, tmW2, b1, b2, X1, xo, fl, 3);
    } else {
      launch(k_mlp, 112, 384, G_SMEM, 16, tmH, tmW1, tmU, tmUs, tmW2, b1, b2, X1, xo, fl, 1);
      launch(k_mlp, 112, 384, G_SMEM, 16, tmH, tmW1, tmU, tmUs, tmW2, b1, b2, X1, xo, fl, 2);
    }
  }
}
```
